```python
import torch

def _softmax(x, axis=-1):
    return torch.softmax(x, dim=axis)
def _gelu(x):
    return torch.nn.functional.gelu(x, approximate="tanh")
def _silu(x):
    return torch.nn.functional.silu(x)
def _sigmoid(x):
    return torch.sigmoid(x)
def _layernorm(x, axis=-1, eps=1e-5):
    m = x.mean(dim=axis, keepdim=True)
    v = x.var(dim=axis, keepdim=True, unbiased=False)
    return (x - m) / torch.sqrt(v + eps)
def _scatter_add(tgt, idx, src, axis=0):
    return tgt.clone().index_add_(axis, idx, src)
def _segment_sum(src, seg, n):
    out = torch.zeros((n,) + src.shape[1:], dtype=src.dtype)
    return out.index_add_(0, seg, src)
def _pad(x, pw):
    flat = tuple(v for pair in reversed(pw) for v in pair)
    return torch.nn.functional.pad(x, flat)

kernel_name = 'sequential_preLN__ssm_conv_h3__dense_activation_gelu__prompt'

def setup_inputs():

    _w = (lambda a: (lambda t: t.to(torch.bfloat16) if t.is_floating_point() else t)(torch.as_tensor(a)))
    def _A_setup():
        B, S, D = 1, 2048, 576
        ks = 4
        return {
            "q": _w((lambda *s: torch.randn(*s, dtype=torch.bfloat16) * 0.05)(B, S, D)),
            "k": _w((lambda *s: torch.randn(*s, dtype=torch.bfloat16) * 0.2)(B, S, D)),
            "v": _w((lambda *s: torch.randn(*s, dtype=torch.bfloat16) * 0.2)(B, S, D)),
            "shift_k": _w((lambda *s: torch.randn(*s, dtype=torch.bfloat16) * 0.2)(D, ks) * 0.5),
            "ssm_k": _w((lambda *s: torch.randn(*s, dtype=torch.bfloat16) * 0.8)(D, S) * (1.0 / S ** 0.5)),
            "ssm_D": _w((lambda *s: torch.randn(*s, dtype=torch.bfloat16) * 0.2)(D)),
        }
    _A_in = _A_setup()

    def _B_setup():
        B, S, D, F = 1, 2048, 576, 4608
        return {
            "x": _w((lambda *s: torch.randn(*s, dtype=torch.bfloat16) * 0.05)(B, S, D)),
            "w1": _w((lambda *s: torch.randn(*s, dtype=torch.bfloat16) * 0.4)(D, F) * (D ** -0.5)),
            "b1": _w((lambda *s: torch.randn(*s, dtype=torch.bfloat16) * 12.8)(F) * 0.01),
            "w2": _w((lambda *s: torch.randn(*s, dtype=torch.bfloat16) * 0.2)(F, D) * (F ** -0.5)),
            "b2": _w((lambda *s: torch.randn(*s, dtype=torch.bfloat16) * 1.6)(D) * 0.01),
        }
    _B_in = _B_setup()

    return {
        "A_q": _A_in["q"],
        "A_k": _A_in["k"],
        "A_v": _A_in["v"],
        "A_shift_k": _A_in["shift_k"],
        "A_ssm_k": _A_in["ssm_k"],
        "A_ssm_D": _A_in["ssm_D"],
        "B_x": _B_in["x"],
        "B_w1": _B_in["w1"],
        "B_b1": _B_in["b1"],
        "B_w2": _B_in["w2"],
        "B_b2": _B_in["b2"],
    }

def reference(A_q, A_k, A_v, A_shift_k, A_ssm_k, A_ssm_D, B_x, B_w1, B_b1, B_w2, B_b2):
    def _A_ref(q, k, v, shift_k, ssm_k, ssm_D):
        B, S, D = q.shape
        ks = shift_k.shape[-1]
        k_pad = _pad(k, ((0, 0), (ks - 1, 0), (0, 0)))
        k_shift = torch.zeros_like(k)
        for t in range(ks):
            k_shift = k_shift + k_pad[:, t:t + S, :] * shift_k[:, ks - 1 - t][None, None, :]
        kv = k_shift * v
        L = 2 * S
        kv_pad = _pad(kv, ((0, 0), (0, S), (0, 0)))
        kf_pad = _pad(ssm_k, ((0, 0), (0, S)))
        kv_f = (lambda x, axes=(-2,-1): torch.fft.rfft2(x.float(), dim=axes))(kv_pad[:, None, :, :], axes=(1, 2))
        kf_f = (lambda x, axes=(-2,-1): torch.fft.rfft2(x.float(), dim=axes))(kf_pad[:, None, :], axes=(1, 2))
        kf_f = (lambda x, *d: x.permute(*d))(kf_f, 1, 2, 0)
        y_f = kv_f * kf_f[None, :, :, :]
        y = (lambda x, s, axes=(-2,-1): torch.fft.irfft2(x, s=s, dim=axes).to(torch.bfloat16))(y_f, (1, L), axes=(1, 2))[:, 0, :S, :]
        y = y + kv * ssm_D[None, None, :]
        return q * y

    def _B_ref(x, w1, b1, w2, b2):
        h = torch.einsum("bsd,df->bsf", x, w1) + b1
        h = _gelu(h)
        return torch.einsum("bsf,fd->bsd", h, w2) + b2

    x = A_q
    h = x + _A_ref(_layernorm(x, axis=-1), A_k, A_v, A_shift_k, A_ssm_k, A_ssm_D)
    h2 = h + _B_ref(_layernorm(h, axis=-1), B_w1, B_b1, B_w2, B_b2)
    return h2
```

```cpp
#include <cuda_runtime.h>
#include <cuda.h>
#include <cuda_bf16.h>
#include <stdint.h>

typedef __nv_bfloat16 bf16;
constexpr int S_ = 2048, D_ = 576, F_ = 4608;

template<int N> struct WGrs;
template<int N> struct WGss;
template<> struct WGrs<32> { template<int OFF,int TB,uint32_t BO,uint32_t BH,int SD,int NA> static __device__ __forceinline__ void mma(float (&d)[NA], uint32_t a0, uint32_t a1, uint32_t a2, uint32_t a3, uint32_t lb) {
  asm volatile("{.reg .pred p; .reg .b32 y; .reg .b64 db; setp.ne.b32 p, %21, 0; add.u32 y, %20, %23; mov.b64 db, {y, %24};\n"
   "wgmma.mma_async.sync.aligned.m64n32k16.f32.bf16.bf16 {%0, %1, %2, %3, %4, %5, %6, %7, %8, %9, %10, %11, %12, %13, %14, %15}, {%16, %17, %18, %19}, db, p, 1, 1, %22;}"
   : "+f"(d[OFF+0]), "+f"(d[OFF+1]), "+f"(d[OFF+2]), "+f"(d[OFF+3]), "+f"(d[OFF+4]), "+f"(d[OFF+5]), "+f"(d[OFF+6]), "+f"(d[OFF+7]), "+f"(d[OFF+8]), "+f"(d[OFF+9]), "+f"(d[OFF+10]), "+f"(d[OFF+11]), "+f"(d[OFF+12]), "+f"(d[OFF+13]), "+f"(d[OFF+14]), "+f"(d[OFF+15])
   : "r"(a0), "r"(a1), "r"(a2), "r"(a3), "r"(lb), "n"(SD), "n"(TB), "n"(BO), "n"(BH)); }
 template<int OFF,int TB,uint32_t BO,uint32_t BH,int NA> static __device__ __forceinline__ void mma_p(float (&d)[NA], uint32_t a0, uint32_t a1, uint32_t a2, uint32_t a3, uint32_t lb, int sd) {
  asm volatile("{.reg .pred p; .reg .b32 y; .reg .b64 db; setp.ne.b32 p, %21, 0; add.u32 y, %20, %23; mov.b64 db, {y, %24};\n"
   "wgmma.mma_async.sync.aligned.m64n32k16.f32.bf16.bf16 {%0, %1, %2, %3, %4, %5, %6, %7, %8, %9, %10, %11, %12, %13, %14, %15}, {%16, %17, %18, %19}, db, p, 1, 1, %22;}"
   : "+f"(d[OFF+0]), "+f"(d[OFF+1]), "+f"(d[OFF+2]), "+f"(d[OFF+3]), "+f"(d[OFF+4]), "+f"(d[OFF+5]), "+f"(d[OFF+6]), "+f"(d[OFF+7]), "+f"(d[OFF+8]), "+f"(d[OFF+9]), "+f"(d[OFF+10]), "+f"(d[OFF+11]), "+f"(d[OFF+12]), "+f"(d[OFF+13]), "+f"(d[OFF+14]), "+f"(d[OFF+15])
   : "r"(a0), "r"(a1), "r"(a2), "r"(a3), "r"(lb), "r"(sd), "n"(TB), "n"(BO), "n"(BH)); } };
template<> struct WGrs<64> { template<int OFF,int TB,uint32_t BO,uint32_t BH,int SD,int NA> static __device__ __forceinline__ void mma(float (&d)[NA], uint32_t a0, uint32_t a1, uint32_t a2, uint32_t a3, uint32_t lb) {
  asm volatile("{.reg .pred p; .reg .b32 y; .reg .b64 db; setp.ne.b32 p, %37, 0; add.u32 y, %36, %39; mov.b64 db, {y, %40};\n"
   "wgmma.mma_async.sync.aligned.m64n64k16.f32.bf16.bf16 {%0, %1, %2, %3, %4, %5, %6, %7, %8, %9, %10, %11, %12, %13, %14, %15, %16, %17, %18, %19, %20, %21, %22, %23, %24, %25, %26, %27, %28, %29, %30, %31}, {%32, %33, %34, %35}, db, p, 1, 1, %38;}"
   : "+f"(d[OFF+0]), "+f"(d[OFF+1]), "+f"(d[OFF+2]), "+f"(d[OFF+3]), "+f"(d[OFF+4]), "+f"(d[OFF+5]), "+f"(d[OFF+6]), "+f"(d[OFF+7]), "+f"(d[OFF+8]), "+f"(d[OFF+9]), "+f"(d[OFF+10]), "+f"(d[OFF+11]), "+f"(d[OFF+12]), "+f"(d[OFF+13]), "+f"(d[OFF+14]), "+f"(d[OFF+15]), "+f"(d[OFF+16]), "+f"(d[OFF+17]), "+f"(d[OFF+18]), "+f"(d[OFF+19]), "+f"(d[OFF+20]), "+f"(d[OFF+21]), "+f"(d[OFF+22]), "+f"(d[OFF+23]), "+f"(d[OFF+24]), "+f"(d[OFF+25]), "+f"(d[OFF+26]), "+f"(d[OFF+27]), "+f"(d[OFF+28]), "+f"(d[OFF+29]), "+f"(d[OFF+30]), "+f"(d[OFF+31])
   : "r"(a0), "r"(a1), "r"(a2), "r"(a3), "r"(lb), "n"(SD), "n"(TB), "n"(BO), "n"(BH)); }
 template<int OFF,int TB,uint32_t BO,uint32_t BH,int NA> static __device__ __forceinline__ void mma_p(float (&d)[NA], uint32_t a0, uint32_t a1, uint32_t a2, uint32_t a3, uint32_t lb, int sd) {
  asm volatile("{.reg .pred p; .reg .b32 y; .reg .b64 db; setp.ne.b32 p, %37, 0; add.u32 y, %36, %39; mov.b64 db, {y, %40};\n"
   "wgmma.mma_async.sync.aligned.m64n64k16.f32.bf16.bf16 {%0, %1, %2, %3, %4, %5, %6, %7, %8, %9, %10, %11, %12, %13, %14, %15, %16, %17, %18, %19, %20, %21, %22, %23, %24, %25, %26, %27, %28, %29, %30, %31}, {%32, %33, %34, %35}, db, p, 1, 1, %38;}"
   : "+f"(d[OFF+0]), "+f"(d[OFF+1]), "+f"(d[OFF+2]), "+f"(d[OFF+3]), "+f"(d[OFF+4]), "+f"(d[OFF+5]), "+f"(d[OFF+6]), "+f"(d[OFF+7]), "+f"(d[OFF+8]), "+f"(d[OFF+9]), "+f"(d[OFF+10]), "+f"(d[OFF+11]), "+f"(d[OFF+12]), "+f"(d[OFF+13]), "+f"(d[OFF+14]), "+f"(d[OFF+15]), "+f"(d[OFF+16]), "+f"(d[OFF+17]), "+f"(d[OFF+18]), "+f"(d[OFF+19]), "+f"(d[OFF+20]), "+f"(d[OFF+21]), "+f"(d[OFF+22]), "+f"(d[OFF+23]), "+f"(d[OFF+24]), "+f"(d[OFF+25]), "+f"(d[OFF+26]), "+f"(d[OFF+27]), "+f"(d[OFF+28]), "+f"(d[OFF+29]), "+f"(d[OFF+30]), "+f"(d[OFF+31])
   : "r"(a0), "r"(a1), "r"(a2), "r"(a3), "r"(lb), "r"(sd), "n"(TB), "n"(BO), "n"(BH)); } };
template<> struct WGrs<96> { template<int OFF,int TB,uint32_t BO,uint32_t BH,int SD,int NA> static __device__ __forceinline__ void mma(float (&d)[NA], uint32_t a0, uint32_t a1, uint32_t a2, uint32_t a3, uint32_t lb) {
  asm volatile("{.reg .pred p; .reg .b32 y; .reg .b64 db; setp.ne.b32 p, %53, 0; add.u32 y, %52, %55; mov.b64 db, {y, %56};\n"
   "wgmma.mma_async.sync.aligned.m64n96k16.f32.bf16.bf16 {%0, %1, %2, %3, %4, %5, %6, %7, %8, %9, %10, %11, %12, %13, %14, %15, %16, %17, %18, %19, %20, %21, %22, %23, %24, %25, %26, %27, %28, %29, %30, %31, %32, %33, %34, %35, %36, %37, %38, %39, %40, %41, %42, %43, %44, %45, %46, %47}, {%48, %49, %50, %51}, db, p, 1, 1, %54;}"
   : "+f"(d[OFF+0]), "+f"(d[OFF+1]), "+f"(d[OFF+2]), "+f"(d[OFF+3]), "+f"(d[OFF+4]), "+f"(d[OFF+5]), "+f"(d[OFF+6]), "+f"(d[OFF+7]), "+f"(d[OFF+8]), "+f"(d[OFF+9]), "+f"(d[OFF+10]), "+f"(d[OFF+11]), "+f"(d[OFF+12]), "+f"(d[OFF+13]), "+f"(d[OFF+14]), "+f"(d[OFF+15]), "+f"(d[OFF+16]), "+f"(d[OFF+17]), "+f"(d[OFF+18]), "+f"(d[OFF+19]), "+f"(d[OFF+20]), "+f"(d[OFF+21]), "+f"(d[OFF+22]), "+f"(d[OFF+23]), "+f"(d[OFF+24]), "+f"(d[OFF+25]), "+f"(d[OFF+26]), "+f"(d[OFF+27]), "+f"(d[OFF+28]), "+f"(d[OFF+29]), "+f"(d[OFF+30]), "+f"(d[OFF+31]), "+f"(d[OFF+32]), "+f"(d[OFF+33]), "+f"(d[OFF+34]), "+f"(d[OFF+35]), "+f"(d[OFF+36]), "+f"(d[OFF+37]), "+f"(d[OFF+38]), "+f"(d[OFF+39]), "+f"(d[OFF+40]), "+f"(d[OFF+41]), "+f"(d[OFF+42]), "+f"(d[OFF+43]), "+f"(d[OFF+44]), "+f"(d[OFF+45]), "+f"(d[OFF+46]), "+f"(d[OFF+47])
   : "r"(a0), "r"(a1), "r"(a2), "r"(a3), "r"(lb), "n"(SD), "n"(TB), "n"(BO), "n"(BH)); }
 template<int OFF,int TB,uint32_t BO,uint32_t BH,int NA> static __device__ __forceinline__ void mma_p(float (&d)[NA], uint32_t a0, uint32_t a1, uint32_t a2, uint32_t a3, uint32_t lb, int sd) {
  asm volatile("{.reg .pred p; .reg .b32 y; .reg .b64 db; setp.ne.b32 p, %53, 0; add.u32 y, %52, %55; mov.b64 db, {y, %56};\n"
   "wgmma.mma_async.sync.aligned.m64n96k16.f32.bf16.bf16 {%0, %1, %2, %3, %4, %5, %6, %7, %8, %9, %10, %11, %12, %13, %14, %15, %16, %17, %18, %19, %20, %21, %22, %23, %24, %25, %26, %27, %28, %29, %30, %31, %32, %33, %34, %35, %36, %37, %38, %39, %40, %41, %42, %43, %44, %45, %46, %47}, {%48, %49, %50, %51}, db, p, 1, 1, %54;}"
   : "+f"(d[OFF+0]), "+f"(d[OFF+1]), "+f"(d[OFF+2]), "+f"(d[OFF+3]), "+f"(d[OFF+4]), "+f"(d[OFF+5]), "+f"(d[OFF+6]), "+f"(d[OFF+7]), "+f"(d[OFF+8]), "+f"(d[OFF+9]), "+f"(d[OFF+10]), "+f"(d[OFF+11]), "+f"(d[OFF+12]), "+f"(d[OFF+13]), "+f"(d[OFF+14]), "+f"(d[OFF+15]), "+f"(d[OFF+16]), "+f"(d[OFF+17]), "+f"(d[OFF+18]), "+f"(d[OFF+19]), "+f"(d[OFF+20]), "+f"(d[OFF+21]), "+f"(d[OFF+22]), "+f"(d[OFF+23]), "+f"(d[OFF+24]), "+f"(d[OFF+25]), "+f"(d[OFF+26]), "+f"(d[OFF+27]), "+f"(d[OFF+28]), "+f"(d[OFF+29]), "+f"(d[OFF+30]), "+f"(d[OFF+31]), "+f"(d[OFF+32]), "+f"(d[OFF+33]), "+f"(d[OFF+34]), "+f"(d[OFF+35]), "+f"(d[OFF+36]), "+f"(d[OFF+37]), "+f"(d[OFF+38]), "+f"(d[OFF+39]), "+f"(d[OFF+40]), "+f"(d[OFF+41]), "+f"(d[OFF+42]), "+f"(d[OFF+43]), "+f"(d[OFF+44]), "+f"(d[OFF+45]), "+f"(d[OFF+46]), "+f"(d[OFF+47])
   : "r"(a0), "r"(a1), "r"(a2), "r"(a3), "r"(lb), "r"(sd), "n"(TB), "n"(BO), "n"(BH)); } };
template<> struct WGrs<128> { template<int OFF,int TB,uint32_t BO,uint32_t BH,int SD,int NA> static __device__ __forceinline__ void mma(float (&d)[NA], uint32_t a0, uint32_t a1, uint32_t a2, uint32_t a3, uint32_t lb) {
  asm volatile("{.reg .pred p; .reg .b32 y; .reg .b64 db; setp.ne.b32 p, %69, 0; add.u32 y, %68, %71; mov.b64 db, {y, %72};\n"
   "wgmma.mma_async.sync.aligned.m64n128k16.f32.bf16.bf16 {%0, %1, %2, %3, %4, %5, %6, %7, %8, %9, %10, %11, %12, %13, %14, %15, %16, %17, %18, %19, %20, %21, %22, %23, %24, %25, %26, %27, %28, %29, %30, %31, %32, %33, %34, %35, %36, %37, %38, %39, %40, %41, %42, %43, %44, %45, %46, %47, %48, %49, %50, %51, %52, %53, %54, %55, %56, %57, %58, %59, %60, %61, %62, %63}, {%64, %65, %66, %67}, db, p, 1, 1, %70;}"
   : "+f"(d[OFF+0]), "+f"(d[OFF+1]), "+f"(d[OFF+2]), "+f"(d[OFF+3]), "+f"(d[OFF+4]), "+f"(d[OFF+5]), "+f"(d[OFF+6]), "+f"(d[OFF+7]), "+f"(d[OFF+8]), "+f"(d[OFF+9]), "+f"(d[OFF+10]), "+f"(d[OFF+11]), "+f"(d[OFF+12]), "+f"(d[OFF+13]), "+f"(d[OFF+14]), "+f"(d[OFF+15]), "+f"(d[OFF+16]), "+f"(d[OFF+17]), "+f"(d[OFF+18]), "+f"(d[OFF+19]), "+f"(d[OFF+20]), "+f"(d[OFF+21]), "+f"(d[OFF+22]), "+f"(d[OFF+23]), "+f"(d[OFF+24]), "+f"(d[OFF+25]), "+f"(d[OFF+26]), "+f"(d[OFF+27]), "+f"(d[OFF+28]), "+f"(d[OFF+29]), "+f"(d[OFF+30]), "+f"(d[OFF+31]), "+f"(d[OFF+32]), "+f"(d[OFF+33]), "+f"(d[OFF+34]), "+f"(d[OFF+35]), "+f"(d[OFF+36]), "+f"(d[OFF+37]), "+f"(d[OFF+38]), "+f"(d[OFF+39]), "+f"(d[OFF+40]), "+f"(d[OFF+41]), "+f"(d[OFF+42]), "+f"(d[OFF+43]), "+f"(d[OFF+44]), "+f"(d[OFF+45]), "+f"(d[OFF+46]), "+f"(d[OFF+47]), "+f"(d[OFF+48]), "+f"(d[OFF+49]), "+f"(d[OFF+50]), "+f"(d[OFF+51]), "+f"(d[OFF+52]), "+f"(d[OFF+53]), "+f"(d[OFF+54]), "+f"(d[OFF+55]), "+f"(d[OFF+56]), "+f"(d[OFF+57]), "+f"(d[OFF+58]), "+f"(d[OFF+59]), "+f"(d[OFF+60]), "+f"(d[OFF+61]), "+f"(d[OFF+62]), "+f"(d[OFF+63])
   : "r"(a0), "r"(a1), "r"(a2), "r"(a3), "r"(lb), "n"(SD), "n"(TB), "n"(BO), "n"(BH)); }
 template<int OFF,int TB,uint32_t BO,uint32_t BH,int NA> static __device__ __forceinline__ void mma_p(float (&d)[NA], uint32_t a0, uint32_t a1, uint32_t a2, uint32_t a3, uint32_t lb, int sd) {
  asm volatile("{.reg .pred p; .reg .b32 y; .reg .b64 db; setp.ne.b32 p, %69, 0; add.u32 y, %68, %71; mov.b64 db, {y, %72};\n"
   "wgmma.mma_async.sync.aligned.m64n128k16.f32.bf16.bf16 {%0, %1, %2, %3, %4, %5, %6, %7, %8, %9, %10, %11, %12, %13, %14, %15, %16, %17, %18, %19, %20, %21, %22, %23, %24, %25, %26, %27, %28, %29, %30, %31, %32, %33, %34, %35, %36, %37, %38, %39, %40, %41, %42, %43, %44, %45, %46, %47, %48, %49, %50, %51, %52, %53, %54, %55, %56, %57, %58, %59, %60, %61, %62, %63}, {%64, %65, %66, %67}, db, p, 1, 1, %70;}"
   : "+f"(d[OFF+0]), "+f"(d[OFF+1]), "+f"(d[OFF+2]), "+f"(d[OFF+3]), "+f"(d[OFF+4]), "+f"(d[OFF+5]), "+f"(d[OFF+6]), "+f"(d[OFF+7]), "+f"(d[OFF+8]), "+f"(d[OFF+9]), "+f"(d[OFF+10]), "+f"(d[OFF+11]), "+f"(d[OFF+12]), "+f"(d[OFF+13]), "+f"(d[OFF+14]), "+f"(d[OFF+15]), "+f"(d[OFF+16]), "+f"(d[OFF+17]), "+f"(d[OFF+18]), "+f"(d[OFF+19]), "+f"(d[OFF+20]), "+f"(d[OFF+21]), "+f"(d[OFF+22]), "+f"(d[OFF+23]), "+f"(d[OFF+24]), "+f"(d[OFF+25]), "+f"(d[OFF+26]), "+f"(d[OFF+27]), "+f"(d[OFF+28]), "+f"(d[OFF+29]), "+f"(d[OFF+30]), "+f"(d[OFF+31]), "+f"(d[OFF+32]), "+f"(d[OFF+33]), "+f"(d[OFF+34]), "+f"(d[OFF+35]), "+f"(d[OFF+36]), "+f"(d[OFF+37]), "+f"(d[OFF+38]), "+f"(d[OFF+39]), "+f"(d[OFF+40]), "+f"(d[OFF+41]), "+f"(d[OFF+42]), "+f"(d[OFF+43]), "+f"(d[OFF+44]), "+f"(d[OFF+45]), "+f"(d[OFF+46]), "+f"(d[OFF+47]), "+f"(d[OFF+48]), "+f"(d[OFF+49]), "+f"(d[OFF+50]), "+f"(d[OFF+51]), "+f"(d[OFF+52]), "+f"(d[OFF+53]), "+f"(d[OFF+54]), "+f"(d[OFF+55]), "+f"(d[OFF+56]), "+f"(d[OFF+57]), "+f"(d[OFF+58]), "+f"(d[OFF+59]), "+f"(d[OFF+60]), "+f"(d[OFF+61]), "+f"(d[OFF+62]), "+f"(d[OFF+63])
   : "r"(a0), "r"(a1), "r"(a2), "r"(a3), "r"(lb), "r"(sd), "n"(TB), "n"(BO), "n"(BH)); } };
template<> struct WGss<64> { template<int OFF,int TA,int TB,uint32_t AO,uint32_t AH,uint32_t BO,uint32_t BH,int SD,int NA> static __device__ __forceinline__ void mma(float (&d)[NA], uint32_t la, uint32_t lb) {
  asm volatile("{.reg .pred p; .reg .b32 x, y; .reg .b64 da, db; setp.ne.b32 p, %34, 0; add.u32 x, %32, %37; mov.b64 da, {x, %38}; add.u32 y, %33, %39; mov.b64 db, {y, %40};\n"
   "wgmma.mma_async.sync.aligned.m64n64k16.f32.bf16.bf16 {%0, %1, %2, %3, %4, %5, %6, %7, %8, %9, %10, %11, %12, %13, %14, %15, %16, %17, %18, %19, %20, %21, %22, %23, %24, %25, %26, %27, %28, %29, %30, %31}, da, db, p, 1, 1, %35, %36;}"
   : "+f"(d[OFF+0]), "+f"(d[OFF+1]), "+f"(d[OFF+2]), "+f"(d[OFF+3]), "+f"(d[OFF+4]), "+f"(d[OFF+5]), "+f"(d[OFF+6]), "+f"(d[OFF+7]), "+f"(d[OFF+8]), "+f"(d[OFF+9]), "+f"(d[OFF+10]), "+f"(d[OFF+11]), "+f"(d[OFF+12]), "+f"(d[OFF+13]), "+f"(d[OFF+14]), "+f"(d[OFF+15]), "+f"(d[OFF+16]), "+f"(d[OFF+17]), "+f"(d[OFF+18]), "+f"(d[OFF+19]), "+f"(d[OFF+20]), "+f"(d[OFF+21]), "+f"(d[OFF+22]), "+f"(d[OFF+23]), "+f"(d[OFF+24]), "+f"(d[OFF+25]), "+f"(d[OFF+26]), "+f"(d[OFF+27]), "+f"(d[OFF+28]), "+f"(d[OFF+29]), "+f"(d[OFF+30]), "+f"(d[OFF+31])
   : "r"(la), "r"(lb), "n"(SD), "n"(TA), "n"(TB), "n"(AO), "n"(AH), "n"(BO), "n"(BH)); } };
template<> struct WGss<96> { template<int OFF,int TA,int TB,uint32_t AO,uint32_t AH,uint32_t BO,uint32_t BH,int SD,int NA> static __device__ __forceinline__ void mma(float (&d)[NA], uint32_t la, uint32_t lb) {
  asm volatile("{.reg .pred p; .reg .b32 x, y; .reg .b64 da, db; setp.ne.b32 p, %50, 0; add.u32 x, %48, %53; mov.b64 da, {x, %54}; add.u32 y, %49, %55; mov.b64 db, {y, %56};\n"
   "wgmma.mma_async.sync.aligned.m64n96k16.f32.bf16.bf16 {%0, %1, %2, %3, %4, %5, %6, %7, %8, %9, %10, %11, %12, %13, %14, %15, %16, %17, %18, %19, %20, %21, %22, %23, %24, %25, %26, %27, %28, %29, %30, %31, %32, %33, %34, %35, %36, %37, %38, %39, %40, %41, %42, %43, %44, %45, %46, %47}, da, db, p, 1, 1, %51, %52;}"
   : "+f"(d[OFF+0]), "+f"(d[OFF+1]), "+f"(d[OFF+2]), "+f"(d[OFF+3]), "+f"(d[OFF+4]), "+f"(d[OFF+5]), "+f"(d[OFF+6]), "+f"(d[OFF+7]), "+f"(d[OFF+8]), "+f"(d[OFF+9]), "+f"(d[OFF+10]), "+f"(d[OFF+11]), "+f"(d[OFF+12]), "+f"(d[OFF+13]), "+f"(d[OFF+14]), "+f"(d[OFF+15]), "+f"(d[OFF+16]), "+f"(d[OFF+17]), "+f"(d[OFF+18]), "+f"(d[OFF+19]), "+f"(d[OFF+20]), "+f"(d[OFF+21]), "+f"(d[OFF+22]), "+f"(d[OFF+23]), "+f"(d[OFF+24]), "+f"(d[OFF+25]), "+f"(d[OFF+26]), "+f"(d[OFF+27]), "+f"(d[OFF+28]), "+f"(d[OFF+29]), "+f"(d[OFF+30]), "+f"(d[OFF+31]), "+f"(d[OFF+32]), "+f"(d[OFF+33]), "+f"(d[OFF+34]), "+f"(d[OFF+35]), "+f"(d[OFF+36]), "+f"(d[OFF+37]), "+f"(d[OFF+38]), "+f"(d[OFF+39]), "+f"(d[OFF+40]), "+f"(d[OFF+41]), "+f"(d[OFF+42]), "+f"(d[OFF+43]), "+f"(d[OFF+44]), "+f"(d[OFF+45]), "+f"(d[OFF+46]), "+f"(d[OFF+47])
   : "r"(la), "r"(lb), "n"(SD), "n"(TA), "n"(TB), "n"(AO), "n"(AH), "n"(BO), "n"(BH)); } };
template<> struct WGss<128> { template<int OFF,int TA,int TB,uint32_t AO,uint32_t AH,uint32_t BO,uint32_t BH,int SD,int NA> static __device__ __forceinline__ void mma(float (&d)[NA], uint32_t la, uint32_t lb) {
  asm volatile("{.reg .pred p; .reg .b32 x, y; .reg .b64 da, db; setp.ne.b32 p, %66, 0; add.u32 x, %64, %69; mov.b64 da, {x, %70}; add.u32 y, %65, %71; mov.b64 db, {y, %72};\n"
   "wgmma.mma_async.sync.aligned.m64n128k16.f32.bf16.bf16 {%0, %1, %2, %3, %4, %5, %6, %7, %8, %9, %10, %11, %12, %13, %14, %15, %16, %17, %18, %19, %20, %21, %22, %23, %24, %25, %26, %27, %28, %29, %30, %31, %32, %33, %34, %35, %36, %37, %38, %39, %40, %41, %42, %43, %44, %45, %46, %47, %48, %49, %50, %51, %52, %53, %54, %55, %56, %57, %58, %59, %60, %61, %62, %63}, da, db, p, 1, 1, %67, %68;}"
   : "+f"(d[OFF+0]), "+f"(d[OFF+1]), "+f"(d[OFF+2]), "+f"(d[OFF+3]), "+f"(d[OFF+4]), "+f"(d[OFF+5]), "+f"(d[OFF+6]), "+f"(d[OFF+7]), "+f"(d[OFF+8]), "+f"(d[OFF+9]), "+f"(d[OFF+10]), "+f"(d[OFF+11]), "+f"(d[OFF+12]), "+f"(d[OFF+13]), "+f"(d[OFF+14]), "+f"(d[OFF+15]), "+f"(d[OFF+16]), "+f"(d[OFF+17]), "+f"(d[OFF+18]), "+f"(d[OFF+19]), "+f"(d[OFF+20]), "+f"(d[OFF+21]), "+f"(d[OFF+22]), "+f"(d[OFF+23]), "+f"(d[OFF+24]), "+f"(d[OFF+25]), "+f"(d[OFF+26]), "+f"(d[OFF+27]), "+f"(d[OFF+28]), "+f"(d[OFF+29]), "+f"(d[OFF+30]), "+f"(d[OFF+31]), "+f"(d[OFF+32]), "+f"(d[OFF+33]), "+f"(d[OFF+34]), "+f"(d[OFF+35]), "+f"(d[OFF+36]), "+f"(d[OFF+37]), "+f"(d[OFF+38]), "+f"(d[OFF+39]), "+f"(d[OFF+40]), "+f"(d[OFF+41]), "+f"(d[OFF+42]), "+f"(d[OFF+43]), "+f"(d[OFF+44]), "+f"(d[OFF+45]), "+f"(d[OFF+46]), "+f"(d[OFF+47]), "+f"(d[OFF+48]), "+f"(d[OFF+49]), "+f"(d[OFF+50]), "+f"(d[OFF+51]), "+f"(d[OFF+52]), "+f"(d[OFF+53]), "+f"(d[OFF+54]), "+f"(d[OFF+55]), "+f"(d[OFF+56]), "+f"(d[OFF+57]), "+f"(d[OFF+58]), "+f"(d[OFF+59]), "+f"(d[OFF+60]), "+f"(d[OFF+61]), "+f"(d[OFF+62]), "+f"(d[OFF+63])
   : "r"(la), "r"(lb), "n"(SD), "n"(TA), "n"(TB), "n"(AO), "n"(AH), "n"(BO), "n"(BH)); } };

__device__ __align__(1024) bf16 g_hT[D_ * S_];
__device__ __align__(1024) float g_cs[F_];
__device__ __align__(1024) float2 g_st2[S_];
__device__ __align__(1024) uint4 g_part[4 * 16 * 8 * 1024];
__device__ unsigned g_epoch;
__device__ unsigned g_epoch1;
__device__ __align__(1024) uint32_t g_st1[S_];

#define DBG(i)
#define DBGH(i)
#define DBG_FLUSH()

__device__ __forceinline__ uint32_t s2u(const void* p) { return (uint32_t)__cvta_generic_to_shared(p); }
__device__ __forceinline__ void mbar_init(uint32_t b, int c) { asm volatile("mbarrier.init.shared::cta.b64 [%0], %1;" ::"r"(b), "r"(c) : "memory"); }
__device__ __forceinline__ void mbar_expect(uint32_t b, int bytes) { asm volatile("mbarrier.arrive.expect_tx.shared::cta.b64 _, [%0], %1;" ::"r"(b), "r"(bytes) : "memory"); }
__device__ __forceinline__ void mbar_arrive(uint32_t b) { asm volatile("mbarrier.arrive.shared::cta.b64 _, [%0];" ::"r"(b) : "memory"); }
__device__ __forceinline__ void mbar_arrive_cluster(uint32_t rb) { asm volatile("mbarrier.arrive.shared::cluster.b64 _, [%0];" ::"r"(rb) : "memory"); }
__device__ __forceinline__ uint32_t mapa(uint32_t a, uint32_t cta) { uint32_t r; asm("mapa.shared::cluster.u32 %0, %1, %2;" : "=r"(r) : "r"(a), "r"(cta)); return r; }
__device__ __forceinline__ void mbar_wait(uint32_t b, int par) {
    asm volatile(
        "{\n.reg .pred p;\n.reg .u32 c;\nmov.u32 c, 0;\n"
        "L_w%=:\n"
        "mbarrier.try_wait.parity.shared::cta.b64 p, [%0], %1;\n"
        "@p bra L_d%=;\n"
        "add.u32 c, c, 1;\nsetp.lt.u32 p, c, 4000000;\n@p bra L_w%=;\ntrap;\n"
        "L_d%=:\n}" ::"r"(b), "r"(par) : "memory");
}
__device__ __forceinline__ void tma2d(uint32_t dst, const CUtensorMap* m, int c0, int c1, uint32_t bar) {
    asm volatile("cp.async.bulk.tensor.2d.shared::cluster.global.mbarrier::complete_tx::bytes [%0], [%1, {%3, %4}], [%2];"
                 ::"r"(dst), "l"(m), "r"(bar), "r"(c0), "r"(c1) : "memory");
}
__device__ __forceinline__ void tma2d_mc(uint32_t dst, const CUtensorMap* m, int c0, int c1, uint32_t bar, uint16_t mask) {
    asm volatile("cp.async.bulk.tensor.2d.shared::cluster.global.mbarrier::complete_tx::bytes.multicast::cluster [%0], [%1, {%3, %4}], [%2], %5;"
                 ::"r"(dst), "l"(m), "r"(bar), "r"(c0), "r"(c1), "h"(mask) : "memory");
}
__device__ __forceinline__ void tma3d(uint32_t dst, const CUtensorMap* m, int c0, int c1, int c2, uint32_t bar) {
    asm volatile("cp.async.bulk.tensor.3d.shared::cluster.global.mbarrier::complete_tx::bytes [%0], [%1, {%3, %4, %5}], [%2];"
                 ::"r"(dst), "l"(m), "r"(bar), "r"(c0), "r"(c1), "r"(c2) : "memory");
}
__device__ __forceinline__ void bulk_g2s(uint32_t dst, const void* src, int bytes, uint32_t bar) {
    asm volatile("cp.async.bulk.shared::cluster.global.mbarrier::complete_tx::bytes [%0], [%1], %2, [%3];"
                 ::"r"(dst), "l"(src), "r"(bytes), "r"(bar) : "memory");
}
__device__ __forceinline__ bool elect_one() { uint32_t p; asm volatile("{.reg .pred q; elect.sync _|q, 0xffffffff; selp.u32 %0, 1, 0, q;}" : "=r"(p)); return p; }
__device__ __forceinline__ void wg_fence() { asm volatile("wgmma.fence.sync.aligned;" ::: "memory"); }
__device__ __forceinline__ void wg_commit() { asm volatile("wgmma.commit_group.sync.aligned;" ::: "memory"); }
template <int N> __device__ __forceinline__ void wg_wait() { asm volatile("wgmma.wait_group.sync.aligned %0;" ::"n"(N) : "memory"); }
#define HD __host__ __device__
HD constexpr uint32_t dlo(uint32_t addr, uint32_t lbo) { return (addr >> 4) | ((lbo >> 4) << 16); }
HD constexpr uint32_t dhi(uint32_t sbo, uint32_t sw) { return (sbo >> 4) | (sw << 30); }
constexpr uint32_t SM0 = 1024;
template <int I> struct IC { static constexpr int v = I; };
template <int A, int B, class Fn> __device__ __forceinline__ void sfor(Fn&& fn) { if constexpr (A < B) { fn(IC<A>{}); sfor<A + 1, B>(fn); } }
template <int NA> __device__ __forceinline__ void reg_fence(float (&a)[NA]) {
#pragma unroll
    for (int i = 0; i < NA; i++) asm volatile("" : "+f"(a[i])::"memory");
}
__device__ __forceinline__ uint32_t pack_bf16(float lo, float hi) { uint32_t r; asm("cvt.rn.bf16x2.f32 %0, %1, %2;" : "=r"(r) : "f"(hi), "f"(lo)); return r; }
__device__ __forceinline__ float bf_lo(uint32_t v) { return __uint_as_float(v << 16); }
__device__ __forceinline__ float bf_hi(uint32_t v) { return __uint_as_float(v & 0xffff0000u); }
__device__ __forceinline__ float tanh_fast(float x) { float r; asm("tanh.approx.f32 %0, %1;" : "=f"(r) : "f"(x)); return r; }
__device__ __forceinline__ float4 lds128f(uint32_t a) { float4 v; asm volatile("ld.shared.v4.f32 {%0,%1,%2,%3}, [%4];" : "=f"(v.x), "=f"(v.y), "=f"(v.z), "=f"(v.w) : "r"(a)); return v; }
__device__ __forceinline__ uint4 lds128u(uint32_t a) { uint4 v; asm volatile("ld.shared.v4.b32 {%0,%1,%2,%3}, [%4];" : "=r"(v.x), "=r"(v.y), "=r"(v.z), "=r"(v.w) : "r"(a)); return v; }
__device__ __forceinline__ float lds32f(uint32_t a) { float v; asm volatile("ld.shared.f32 %0, [%1];" : "=f"(v) : "r"(a)); return v; }
__device__ __forceinline__ void sts128f(uint32_t a, float x, float y, float z, float w) { asm volatile("st.shared.v4.f32 [%0], {%1,%2,%3,%4};" ::"r"(a), "f"(x), "f"(y), "f"(z), "f"(w) : "memory"); }
__device__ __forceinline__ float tagf(float x, uint32_t par) { return __uint_as_float((__float_as_uint(x) & ~1u) | par); }
__device__ __forceinline__ uint4 ld_tagged(const uint4* p) {
    uint4 v;
    asm volatile("{.reg .b128 t; ld.relaxed.gpu.global.b128 t, [%4]; mov.b128 {%0,%1,%2,%3}, t;}" : "=r"(v.x), "=r"(v.y), "=r"(v.z), "=r"(v.w) : "l"(p) : "memory");
    return v;
}
__device__ __forceinline__ void st_tagged(uint4* p, uint32_t x, uint32_t y, uint32_t z, uint32_t w, uint32_t par) {
    asm volatile("{.reg .b128 t; mov.b128 t, {%1,%2,%3,%4}; st.relaxed.gpu.global.b128 [%0], t;}" ::"l"(p), "r"((x & ~1u) | par), "r"(y), "r"(z), "r"(w) : "memory");
}
__device__ __forceinline__ void cp16(uint32_t dst, const void* src) { asm volatile("cp.async.cg.shared.global [%0], [%1], 16;" ::"r"(dst), "l"(src) : "memory"); }
__device__ __forceinline__ void fence_async_smem() { asm volatile("fence.proxy.async.shared::cta;" ::: "memory"); }
__device__ __forceinline__ float bf_round(float x) { return bf_lo(pack_bf16(x, 0.f)); }
__device__ __forceinline__ float rcp_fast(float x) { float r; asm("rcp.approx.ftz.f32 %0, %1;" : "=f"(r) : "f"(x)); return r; }
__device__ __forceinline__ float sqrt_fast(float x) { float r; asm("sqrt.approx.ftz.f32 %0, %1;" : "=f"(r) : "f"(x)); return r; }
__device__ __forceinline__ uint32_t lds32u(uint32_t a) { uint32_t v; asm volatile("ld.shared.b32 %0, [%1];" : "=r"(v) : "r"(a)); return v; }
__device__ __forceinline__ void sts128u(uint32_t a, uint32_t x, uint32_t y, uint32_t z, uint32_t w) { asm volatile("st.shared.v4.b32 [%0], {%1,%2,%3,%4};" ::"r"(a), "r"(x), "r"(y), "r"(z), "r"(w) : "memory"); }

namespace ffn {
constexpr int A_OFF = 0, A_WG = 73728;
constexpr int W_OFF = 147456, W_ST = 12288, NST = 6;
constexpr int BX_OFF = 221184, BX_COLS = 384;
constexpr int AX_OFF = 227328;
constexpr int RS_OFF = 229376;
constexpr int ST_OFF = 229888;
constexpr int B2_OFF = 230144;
constexpr int BAR_OFF = 230656;
constexpr int SMEM = 231168;
constexpr int B_FULLW = 0, B_EMPTYW = 6, B_FULLA = 12, B_PFULL = 21, B_PE = 29, B_STAT = 31, B_Z = 32, B_BXF = 33, B_P1D = 41, B_TICK = 42, B_BXE = 43, B_N = 44;

#define CHUNKS 128, 128, 96, 96, 64, 64
#define NOJOBS 0
#define SFAST 0
#define LDLAG 0
#define XLAG 0
#define AUGD 0
HD constexpr int chunkN(int c) { constexpr int a[] = {CHUNKS, 0}; return a[c]; }
HD constexpr int numChunks() { int n = 0; while (chunkN(n)) n++; return n; }
constexpr int NCH = numChunks();
HD constexpr int chunkCol(int c) { int a = 0; for (int i = 0; i < c; i++) a += chunkN(i); return a; }
HD constexpr int chunkKS(int c) { return 6144 / chunkN(c); }
HD constexpr int chunkNS(int c) { return 576 / chunkKS(c); }
HD constexpr int chunkSt0(int c) { int a = 0; for (int i = 0; i < c; i++) a += chunkNS(i); return a; }
static_assert(chunkCol(NCH) == 576 && chunkSt0(NCH) == 54 && NCH <= 8, "chunks");
HD constexpr int bxWrap() { int c = 0; while (chunkCol(c + 1) <= BX_COLS) c++; return c; }
HD constexpr int bxCol(int c) { return c < bxWrap() ? chunkCol(c) : chunkCol(c) - chunkCol(bxWrap()); }
static_assert(bxWrap() >= 3 && 576 - chunkCol(bxWrap()) <= chunkCol(2), "bx");
HD constexpr uint64_t packTab(int what) {
    uint64_t r = 0;
    for (int c = 0; c < NCH; c++) r |= (uint64_t)(what == 0 ? chunkN(c) / 32 : what == 1 ? chunkCol(c) / 32 : bxCol(c) / 32) << (8 * c);
    return r;
}

struct Ctx {
    uint32_t bar;
    uint32_t aD;
    uint32_t xD;
    bool lead;
    float k00, k01, k10, k11;
};

template <int COL0, int J0, int J1, int NA>
__device__ __forceinline__ void gelu_range(const Ctx& c, const float (&acc)[NA], uint32_t (&H)[144]) {
#pragma unroll
    for (int j = J0; j < J1; j++) {
        const float k0 = (j & 1) ? c.k01 : c.k00, k1 = (j & 1) ? c.k11 : c.k10;
        const float a = acc[2 * j], b = acc[2 * j + 1];
        const float ya = fmaf(a, tanh_fast(a * fmaf(a * a, k1, k0)), a);
        const float yb = fmaf(b, tanh_fast(b * fmaf(b * b, k1, k0)), b);
        H[COL0 / 4 + j] = pack_bf16(ya, yb);
        asm volatile("" : "+r"(H[COL0 / 4 + j])::"memory");
    }
}
template <int C>
__device__ __forceinline__ void aug_mma(const Ctx& c, float (&acc)[chunkN(C) / 2]) {
    WGss<chunkN(C)>::template mma<0, 0, 0, dlo(SM0 + AX_OFF, 0), dhi(128, 0), dlo(SM0 + BX_OFF + bxCol(C) * 16, 0), dhi(128, 0), 1>(acc, c.xD, 0);
}
template <int C, int s>
__device__ __forceinline__ void p1_mma(const Ctx& c, float (&acc)[chunkN(C) / 2]) {
    constexpr int N = chunkN(C), KS = chunkKS(C), gs = chunkSt0(C) + s;
    if constexpr (s == chunkNS(C) - 1) mbar_wait(c.bar + 8 * (B_BXF + C), 0);
    mbar_wait(c.bar + 8 * (B_FULLW + gs % NST), (gs / NST) & 1);
    wg_fence();
    sfor<0, KS / 16>([&](auto kk) {
        constexpr int k = kk.v;
        constexpr uint32_t wb = SM0 + W_OFF + (gs % NST) * W_ST;
        constexpr uint32_t bo = (N == 96) ? dlo(wb + k * 1024, KS * 64) : dlo(wb + k * 2048, KS * 128);
        constexpr uint32_t bh = (N == 96) ? dhi(512, 2) : dhi(1024, 1);
        WGss<N>::template mma<0, 1, 1, dlo(SM0 + A_OFF + (s * KS + k * 16) * 128, 0), dhi(1024, 1), bo, bh, (s | k) != 0>(acc, c.aD, 0);
    });
    if constexpr (s == chunkNS(C) - 1) aug_mma<C>(c, acc);
}
__device__ __forceinline__ void retire(const Ctx& c, int slot) {
    wg_wait<1>();
    if (c.lead) mbar_arrive(c.bar + 8 * (B_EMPTYW + slot));
}

__device__ __forceinline__ void chunk0(const Ctx& c, float (&acc)[chunkN(0) / 2]) {
    constexpr int N = chunkN(0), KS = chunkKS(0);
    static_assert(KS <= 64, "");
    int slot = 0, par = 0, prev = 0;
#pragma unroll 1
    for (int s = 0; s < chunkNS(0); s++) {
        mbar_wait(c.bar + 8 * (B_FULLA + ((s * KS + KS - 1) >> 6)), 0);
        mbar_wait(c.bar + 8 * (B_FULLW + slot), par);
        if (s == 0) DBG(16);
        wg_fence();
        sfor<0, KS / 16>([&](auto kk) {
            constexpr int k = kk.v;
            constexpr uint32_t wb = SM0 + W_OFF;
            constexpr uint32_t bo = (N == 96) ? dlo(wb + k * 1024, KS * 64) : dlo(wb + k * 2048, KS * 128);
            constexpr uint32_t bh = (N == 96) ? dhi(512, 2) : dhi(1024, 1);
            WGss<N>::template mma<0, 1, 1, dlo(SM0 + A_OFF + k * 2048, 0), dhi(1024, 1), bo, bh, 1>(acc, c.aD + s * (KS * 8), slot * (W_ST >> 4));
        });
        wg_commit();
        wg_wait<1>();
        if (c.lead && s > 0) mbar_arrive(c.bar + 8 * (B_EMPTYW + prev));
        prev = slot;
        if (++slot == NST) { slot = 0; par ^= 1; }
    }
}

template <int C, int s, int S0>
__device__ __forceinline__ void chunk_loop(const Ctx& c, float (&acc)[chunkN(C) / 2], float (&prev)[chunkN(C - 1) / 2], uint32_t (&H)[144]) {
    if constexpr (s < chunkNS(C)) {
        constexpr int NP = chunkN(C - 1) / 4, NS = chunkNS(C) - S0;
        p1_mma<C, s>(c, acc);
        wg_commit();
        if constexpr (s >= S0) gelu_range<chunkCol(C - 1), ((s - S0) * NP) / NS, ((s - S0 + 1) * NP) / NS>(c, prev, H);
        retire(c, (chunkSt0(C) + s + NST - 1) % NST);
        if constexpr (s == S0 - 1) reg_fence(prev);
        if constexpr (C == 2 && s == 0) { if (c.lead) mbar_arrive(c.bar + 8 * B_BXE); }
        chunk_loop<C, s + 1, S0>(c, acc, prev, H);
    }
}

template <int PAR, int s, bool DYN = false>
__device__ __forceinline__ void p2_issue(const Ctx& c, float (&acc)[32], const uint32_t (&H)[144], int keep = 0) {
    mbar_wait(c.bar + 8 * (B_FULLW + s), PAR);
    wg_fence();
    sfor<0, 6>([&](auto kk) {
        constexpr int k = kk.v, h0 = s * 24 + 4 * k;
        if constexpr (DYN && k == 0)
            WGrs<64>::template mma_p<0, 1, dlo(SM0 + W_OFF + s * W_ST, 0), dhi(1024, 1)>(acc, H[h0], H[h0 + 1], H[h0 + 2], H[h0 + 3], 0, keep);
        else
            WGrs<64>::template mma<0, 1, dlo(SM0 + W_OFF + s * W_ST + k * 2048, 0), dhi(1024, 1), (s | k) != 0>(acc, H[h0], H[h0 + 1], H[h0 + 2], H[h0 + 3], 0);
    });
    wg_commit();
}

template <int C>
__device__ __forceinline__ void phase1_rest(Ctx& c, float (&prev)[chunkN(C - 1) / 2], uint32_t (&H)[144], float (&accA)[32], uint32_t pe0Remote) {
    if constexpr (C < NCH) {
        DBG(9 + C);
        float acc[chunkN(C) / 2];
        chunk_loop<C, 0, 1>(c, acc, prev, H);
        phase1_rest<C + 1>(c, acc, H, accA, pe0Remote);
    } else {
        constexpr int NP = chunkN(C - 1) / 4, COL = chunkCol(C - 1);
        constexpr int NS = COL / 96 - 1;
        DBG(3);
        sfor<0, 6>([&](auto ss) {
            constexpr int s = ss.v;
            p2_issue<1, s>(c, accA, H);
            if constexpr (s > 0 && s <= NS) gelu_range<COL, ((s - 1) * NP) / NS, (s * NP) / NS>(c, prev, H);
            retire(c, (s + 5) % 6);
            if constexpr (s == 0) {
                reg_fence(prev);
                if (c.lead) mbar_arrive_cluster(pe0Remote);
            }
        });
    }
}

__device__ __forceinline__ uint32_t bufoff(int b, int f) { return (((f >> 1) + 1 + b) & 3) * 16384; }

struct Maps { CUtensorMap w1[3], w2, h; };

__global__ void __launch_bounds__(384, 1) __cluster_dims__(2, 1, 1)
ffn_kernel(const __grid_constant__ Maps mp, const bf16* __restrict__ b1, const bf16* __restrict__ w2, const bf16* __restrict__ b2, bf16* __restrict__ out) {
    extern __shared__ __align__(1024) unsigned char smem_raw[];
    const uint32_t sb = s2u(smem_raw);
    if ((sb & 0xFFFFFF) != SM0) __trap();
    const uint32_t bar = sb + BAR_OFF;
    const int wid = __shfl_sync(0xffffffffu, threadIdx.x >> 5, 0);
    const int lane = threadIdx.x & 31;
    if (blockIdx.x < 4) {
        if (wid >= 4) return;
        const uint32_t par = (__ldcg(&g_epoch1) + 1) & 1;
        auto load = [&](int i) {
            const int b = i % 3;
            mbar_expect(bar + 8 * b, A_WG);
#pragma unroll 1
            for (int s = 0; s < 6; s++) tma3d(sb + b * A_WG + s * W_ST, &mp.w1[0], 0, s * 96, (blockIdx.x * 2 + (i & 1)) * 9 + (i >> 1), bar + 8 * b);
        };
        if (wid < 3 && elect_one()) { mbar_init(bar + 8 * wid, 1); fence_async_smem(); load(wid); }
        asm volatile("bar.sync 1, 128;" ::: "memory");
#pragma unroll 1
        for (int i = 0; i < 18; i++) {
            float acc[32];
#pragma unroll
            for (int j = 0; j < 32; j++) acc[j] = 0.f;
            mbar_wait(bar + 8 * (i % 3), (i / 3) & 1);
            wg_fence();
#pragma unroll 1
            for (int k = 0; k < 36; k++) WGrs<64>::template mma<0, 1, dlo(SM0, 0), dhi(1024, 1), 1>(acc, 0x3f803f80u, 0x3f803f80u, 0x3f803f80u, 0x3f803f80u, (i % 3) * (A_WG >> 4) + k * 128);
            wg_commit();
            wg_wait<0>();
            reg_fence(acc);
            asm volatile("bar.sync 1, 128;" ::: "memory");
            if (wid == 1 && i + 3 < 18 && elect_one()) load(i + 3);
            if (threadIdx.x < 4) {
                float* o = g_cs + ((blockIdx.x * 2 + (i & 1)) * 9 + (i >> 1)) * 64 + 2 * lane;
#pragma unroll
                for (int j = 0; j < 8; j++) asm volatile("st.relaxed.gpu.global.v2.f32 [%0], {%1, %2};" ::"l"(o + 8 * j), "f"(tagf(acc[4 * j], par)), "f"(tagf(acc[4 * j + 1], par)) : "memory");
            }
        }
        return;
    }
    const int bid = blockIdx.x - 4;
    const int m = bid >> 3, f = bid & 7, r = f & 1;
    const int zb = f ^ 1;
    DBG(0);
    if (elect_one()) {
        if (wid < NST) {
            constexpr int N = chunkN(0);
            mbar_init(bar + 8 * (B_FULLW + wid), 1);
            fence_async_smem();
            tma3d(sb + W_OFF + wid * W_ST, &mp.w1[N / 32 - 2], 0, wid * chunkKS(0), N == 96 ? f * 18 : f * 9, bar + 8 * (B_FULLW + wid));
            mbar_expect(bar + 8 * (B_FULLW + wid), W_ST);
        } else if (wid < NST + 5) {
            asm volatile("prefetch.tensormap [%0];" ::"l"(&mp.w1[0] + (wid - NST)) : "memory");
        }
#pragma unroll 1
        for (int i = B_EMPTYW + 11 - wid; i < B_N; i += 12)
            mbar_init(bar + 8 * i, (i < B_FULLA || i >= B_P1D) ? 8 : (i == B_PE || i == B_PE + 1) ? 4 : i == B_Z ? 3 : 1);
        asm volatile("fence.mbarrier_init.release.cluster;" ::: "memory");
    }
    __syncwarp();
    asm volatile("barrier.cluster.arrive.relaxed.aligned;" ::: "memory");

    if (wid >= 8) {
        asm volatile("setmaxnreg.dec.sync.aligned.u32 24;");
        if (wid == 8) {
            asm volatile("barrier.cluster.wait.aligned;" ::: "memory");
            int slot = 0, par = 0, k = NST * chunkKS(0);
#pragma unroll 1
            for (int C = 0; C < NCH; C++) {
                const int n32 = (packTab(0) >> (8 * C)) & 255, c32 = (packTab(1) >> (8 * C)) & 255;
                const int ks = n32 == 2 ? 96 : n32 == 3 ? 64 : 48, g = n32 == 3 ? f * 18 + c32 : f * 9 + (c32 >> 1);
#pragma unroll 1
                for (; k < 576; k += ks) {
                    mbar_wait(bar + 8 * (B_EMPTYW + slot), par);
                    if (elect_one()) {
                        tma3d(sb + W_OFF + slot * W_ST, &mp.w1[n32 - 2], 0, k, g, bar + 8 * (B_FULLW + slot));
                        mbar_expect(bar + 8 * (B_FULLW + slot), W_ST);
                    }
                    if (++slot == NST) { slot = 0; par ^= 1; }
                }
                k = 0;
            }
#pragma unroll 1
            for (int p = 0; p < 9; p++) {
                const int blk = p == 0 ? 8 : 2 * (((f >> 1) + ((p + 1) >> 1)) & 3) + ((p & 1) ^ r);
#pragma unroll 1
                for (int s = 0; s < 6; s++) {
                    mbar_wait(bar + 8 * (B_EMPTYW + s), p & 1);
                    if (elect_one()) {
                        tma2d(sb + W_OFF + s * W_ST, &mp.w2, blk * 64, f * 576 + s * 96, bar + 8 * (B_FULLW + s));
                        mbar_expect(bar + 8 * (B_FULLW + s), W_ST);
                    }
                }
            }
        } else {
            const int hw = wid - 9;
            const uint32_t bb2 = *(const uint32_t*)(b2 + (hw ? 512 : zb * 64) + 2 * lane);
            asm volatile("barrier.cluster.wait.aligned;" ::: "memory");
            asm volatile("griddepcontrol.wait;" ::: "memory");
            DBGH(hw == 0 ? 30 : 31);
            if (elect_one()) {
#pragma unroll 1
                for (int i = hw; i < 9; i += 3) {
                    tma2d_mc(sb + A_OFF + r * A_WG + i * 8192, &mp.h, m * 128 + r * 64, i * 64, bar + 8 * (B_FULLA + i), 3);
                    mbar_expect(bar + 8 * (B_FULLA + i), 16384);
                }
                if (hw < 2) {
#pragma unroll 1
                    for (int i = 0; i < 4; i++) mbar_expect(bar + 8 * (B_PFULL + hw * 4 + i), 16384);
                }
            }
            __syncwarp();
            const unsigned ep = __ldcg(&g_epoch);
            if (hw < 2) asm volatile("st.shared.v2.f32 [%0], {%1, %2};" ::"r"(sb + B2_OFF + hw * 256 + lane * 8), "f"(bf_lo(bb2)), "f"(bf_hi(bb2)) : "memory");
            {
                const int q = lane & 3, ds = ((lane >> 1) & 6) | (lane >> 4);
                const uint32_t la = sb + A_OFF + (f >> 2) * A_WG + ds * 128 + (((2 * (f & 3) + (q >> 1)) ^ ds) << 4) + (q & 1) * 8;
                float v[8];
#pragma unroll
                for (int i = 0; i < 8; i++) v[i] = 0.f;
#pragma unroll 1
                for (int i = hw; i < 9; i += 3) {
                    mbar_wait(bar + 8 * (B_FULLA + i), 0);
#pragma unroll 2
                    for (int j = 0; j < 8; j++) {
                        uint32_t w0, w1;
                        asm volatile("ld.shared.v2.b32 {%0,%1}, [%2];" : "=r"(w0), "=r"(w1) : "r"(la + i * 8192 + j * 1024));
                        const float a0 = bf_lo(w0), a1 = bf_hi(w0), a2 = bf_lo(w1), a3 = bf_hi(w1);
                        v[0] += a0; v[1] += a1; v[2] += a2; v[3] += a3;
                        v[4] = fmaf(a0, a0, v[4]); v[5] = fmaf(a1, a1, v[5]); v[6] = fmaf(a2, a2, v[6]); v[7] = fmaf(a3, a3, v[7]);
                    }
                }
                const bool b4 = lane & 16, b3 = lane & 8, b2_ = lane & 4;
#pragma unroll
                for (int i = 0; i < 4; i++) v[i] = (b4 ? v[4 + i] : v[i]) + __shfl_xor_sync(0xffffffffu, b4 ? v[i] : v[4 + i], 16);
#pragma unroll
                for (int i = 0; i < 2; i++) v[i] = (b3 ? v[2 + i] : v[i]) + __shfl_xor_sync(0xffffffffu, b3 ? v[i] : v[2 + i], 8);
                v[0] = (b2_ ? v[1] : v[0]) + __shfl_xor_sync(0xffffffffu, b2_ ? v[0] : v[1], 4);
                if (hw < 2) {
                    asm volatile("st.shared.f32 [%0], %1;" ::"r"(sb + ST_OFF + hw * 128 + lane * 4), "f"(v[0]) : "memory");
                    asm volatile("bar.arrive 1, 96;" ::: "memory");
                } else {
                    asm volatile("bar.sync 1, 96;" ::: "memory");
                    const float t = (v[0] + lds32f(sb + ST_OFF + lane * 4) + lds32f(sb + ST_OFF + 128 + lane * 4)) * (1.f / D_);
                    const float sq = __shfl_xor_sync(0xffffffffu, t, 16);
                    if (!b4) {
                        const float sg = sqrt_fast(fmaxf(sq - t * t, 0.f) + 1e-5f);
                        asm volatile("st.relaxed.gpu.global.v2.f32 [%0], {%1, %2};" ::"l"(g_st2 + m * 128 + f * 16 + 4 * q + ((lane >> 2) & 1) + ((lane >> 2) & 2)), "f"(tagf(t, ep & 1)), "f"(tagf(sg, ep & 1)) : "memory");
                    }
                }
            }
            const uint32_t par = __shfl_sync(0xffffffffu, ep & 1, 0);
            if (hw == 2) {
                float2 st[4];
#pragma unroll 1
                for (int it = 0; it < 4000000; it++) {
                    uint32_t bad = 0;
#pragma unroll
                    for (int i = 0; i < 4; i++) {
                        asm volatile("ld.relaxed.gpu.global.v2.f32 {%0, %1}, [%2];" : "=f"(st[i].x), "=f"(st[i].y) : "l"(g_st2 + m * 128 + i * 32 + lane) : "memory");
                        bad |= (__float_as_uint(st[i].x) ^ par) | (__float_as_uint(st[i].y) ^ par);
                    }
                    if (!__any_sync(0xffffffffu, bad & 1)) break;
                }
#pragma unroll
                for (int i = 0; i < 4; i++) {
                    const float hs = 0.5f * st[i].y, nm = -0.5f * st[i].x;
                    const float sh = bf_round(hs), mh = bf_round(nm), ml = bf_round(nm - mh);
                    const uint32_t mm = pack_bf16(mh, ml);
                    sts128u(sb + AX_OFF + (i * 32 + lane) * 16, pack_bf16(sh, hs - sh), mm, mm, pack_bf16(nm - mh - ml, mh));
                    asm volatile("st.shared.f32 [%0], %1;" ::"r"(sb + RS_OFF + (i * 32 + lane) * 4), "f"(rcp_fast(st[i].y)) : "memory");
                }
                if (lane == 0) asm volatile("st.shared.b32 [%0], %1;" ::"r"(sb + BAR_OFF + 504), "r"(par) : "memory");
                fence_async_smem();
                __syncwarp();
                if (lane == 0) mbar_arrive(bar + 8 * B_STAT);
            } else if (hw == 1) {
                if (lane < 9)
                    asm volatile("cp.async.bulk.prefetch.L2.global [%0], %1;" ::"l"(w2 + (size_t)(f * 576 + m * 36 + lane * 4) * 576), "r"(4608) : "memory");
            } else {
#pragma unroll 1
                for (int C = 0; C < NCH; C++) {
                    const int n32 = (packTab(0) >> (8 * C)) & 255, col = f * 576 + ((packTab(1) >> (8 * C)) & 255) * 32 + lane;
                    const uint32_t a = sb + BX_OFF + ((packTab(2) >> (8 * C)) & 255) * 512 + lane * 16;
                    float cs[4]; uint32_t bv[4];
#pragma unroll 1
                    for (int it = 0; it < 4000000; it++) {
                        uint32_t bad = 0;
#pragma unroll
                        for (int i = 0; i < 4; i++) {
                            const int ci = col + (i < n32 ? i * 32 : 0);
                            asm volatile("ld.relaxed.gpu.global.f32 %0, [%1];" : "=f"(cs[i]) : "l"(g_cs + ci) : "memory");
                            bv[i] = ((const unsigned short*)b1)[ci];
                            bad |= __float_as_uint(cs[i]) ^ par;
                        }
                        if (!__any_sync(0xffffffffu, bad & 1)) break;
                    }
                    if (C == bxWrap()) mbar_wait(bar + 8 * B_BXE, 0);
#pragma unroll
                    for (int i = 0; i < 4; i++) {
                        const float ch = bf_round(cs[i]), cl = bf_round(cs[i] - ch);
                        if (i < n32) sts128u(a + i * 512, bv[i] * 0x10001u, pack_bf16(ch, ch), pack_bf16(cl, cl), pack_bf16(ch, cs[i] - ch - cl));
                    }
                    fence_async_smem();
                    __syncwarp();
                    if (lane == 0) mbar_arrive(bar + 8 * (B_BXF + C));
                }
            }
            uint32_t lm = (lane & 7) * 128 + ((((lane >> 3) & 1) ^ (lane & 7)) << 4);
            uint32_t tq = sb + (lane & 3) * 8, tg = sb + (lane >> 2) * 4;
            asm volatile("" : "+r"(lm), "+r"(tq), "+r"(tg));
            mbar_wait(bar + 8 * B_P1D, 0);
            DBGH((hw & 1) * 64 + 26);
#pragma unroll 1
            for (int w = hw; w < 8; w += 3) {
                const float s0 = 2.0f * rcp_fast(lds32f(tg + RS_OFF + w * 64)), s1 = 2.0f * rcp_fast(lds32f(tg + RS_OFF + w * 64 + 32));
                const uint32_t aw = sb + A_OFF + (w >> 2) * A_WG;
                const uint32_t ha = aw + zb * 8192 + (lm ^ ((w & 3) << 5));
                const uint32_t ya = aw + bufoff(2, f) + (w & 3) * 512 + lane * 16;
#pragma unroll 2
                for (int j = 0; j < 8; j++) {
                    uint32_t h0, h1;
                    asm volatile("ldmatrix.sync.aligned.m8n8.x2.trans.shared.b16 {%0,%1}, [%2];" : "=r"(h0), "=r"(h1) : "r"(ha + j * 1024));
                    float b0, b1;
                    asm volatile("ld.shared.v2.f32 {%0,%1}, [%2];" : "=f"(b0), "=f"(b1) : "r"(tq + B2_OFF + j * 32));
                    sts128f(ya + j * 2048, (bf_lo(h0) + b0) * s0, (bf_hi(h0) + b1) * s0, (bf_lo(h1) + b0) * s1, (bf_hi(h1) + b1) * s1);
                }
            }
            __syncwarp();
            if (lane == 0) mbar_arrive(bar + 8 * B_Z);
            DBGH((hw & 1) * 64 + 27);
            mbar_wait(bar + 8 * B_TICK, 0);
            mbar_wait(bar + 8 * B_Z, 0);
            DBGH((hw & 1) * 64 + 28);
            const uint32_t ring = sb + A_OFF + (hw >> 1) * A_WG + zb * 8192 + (hw & 1) * 4096 + lane * 16;
#pragma unroll 1
            for (int d = hw; d < (NOJOBS ? 0 : 4); d += 3) {
                float a[8];
#pragma unroll 1
                for (int it = 0; it < 1000000; it++) {
                    const uint4* g = g_part + (size_t)(m * 8) * 1024 + f * 128 + d * 32 + lane;
#pragma unroll 1
                    for (int i = 0; i < 8; i++) { cp16(ring + i * 512, g + i * 1024); __nanosleep(40); }
                    asm volatile("cp.async.wait_all;" ::: "memory");
                    uint32_t bad = 0;
#pragma unroll
                    for (int i = 0; i < 8; i++) a[i] = 0.f;
#pragma unroll 1
                    for (int i = 0; i < 8; i++) {
                        const uint4 v = lds128u(ring + i * 512);
                        bad |= v.x ^ par;
                        a[0] += bf_lo(v.x); a[1] += bf_hi(v.x); a[2] += bf_lo(v.y); a[3] += bf_hi(v.y);
                        a[4] += bf_lo(v.z); a[5] += bf_hi(v.z); a[6] += bf_lo(v.w); a[7] += bf_hi(v.w);
                    }
                    if (!__any_sync(0xffffffffu, bad & 1)) break;
                }
                const float r0 = 0.5f * lds32f(tg + RS_OFF + f * 64), r1 = 0.5f * lds32f(tg + RS_OFF + f * 64 + 32);
                bf16* o = out + (size_t)(m * 128 + f * 16 + (lane >> 2)) * D_ + 512 + 16 * d + 2 * (lane & 3);
#pragma unroll
                for (int u = 0; u < 2; u++) {
                    uint32_t h0, h1;
                    asm volatile("ldmatrix.sync.aligned.m8n8.x2.trans.shared.b16 {%0,%1}, [%2];" : "=r"(h0), "=r"(h1)
                                 : "r"(sb + A_OFF + (f >> 2) * A_WG + 8 * 8192 + (2 * d + u) * 1024 + (lm ^ ((f & 3) << 5))));
                    float b0, b1;
                    asm volatile("ld.shared.v2.f32 {%0,%1}, [%2];" : "=f"(b0), "=f"(b1) : "r"(tq + B2_OFF + 256 + (2 * d + u) * 32));
                    *(uint32_t*)(o + 8 * u) = pack_bf16(fmaf(a[4 * u], r0, bf_lo(h0) + b0), fmaf(a[4 * u + 1], r0, bf_hi(h0) + b1));
                    *(uint32_t*)(o + 8 * u + 8 * D_) = pack_bf16(fmaf(a[4 * u + 2], r1, bf_lo(h1) + b0), fmaf(a[4 * u + 3], r1, bf_hi(h1) + b1));
                }
            }
            if (bid == 0 && threadIdx.x == 288) g_epoch1 = ep;
            DBGH((hw & 1) * 64 + 29);
        }
    } else {
        asm volatile("setmaxnreg.inc.sync.aligned.u32 240;");
        asm volatile("barrier.cluster.wait.aligned;" ::: "memory");
        Ctx c;
        const int wg = wid >> 2, warp = wid & 3;
        c.bar = bar; c.lead = lane == 0;
        c.aD = wg * (A_WG >> 4); c.xD = wg * 64;
        uint32_t H[144];
        float accA[32], accB[32];
        {
            float acc0[chunkN(0) / 2], acc1[chunkN(1) / 2];
#pragma unroll
            for (int i = 0; i < chunkN(0) / 2; i++) acc0[i] = 0.f;
            DBG(1);
            chunk0(c, acc0);
            DBG(2);
            sfor<0, AUGD + 1>([&](auto ss) {
                constexpr int s = ss.v;
                if constexpr (s == AUGD) { mbar_wait(bar + 8 * B_BXF, 0); mbar_wait(bar + 8 * B_STAT, 0); DBG(17); }
                p1_mma<1, s>(c, acc1);
                if constexpr (s == AUGD) aug_mma<0>(c, acc0);
                wg_commit();
                retire(c, (chunkSt0(1) + s + NST - 1) % NST);
            });
            const float r0 = lds32f(sb + RS_OFF + (wid * 16 + (lane >> 2)) * 4), r1 = lds32f(sb + RS_OFF + (wid * 16 + 8 + (lane >> 2)) * 4);
            c.k00 = 0.7978845608028654f * r0; c.k01 = 0.7978845608028654f * r1;
            c.k10 = 0.044715f * c.k00 * r0 * r0; c.k11 = 0.044715f * c.k01 * r1 * r1;
            chunk_loop<1, AUGD + 1, AUGD + 2>(c, acc1, acc0, H);
            phase1_rest<2>(c, acc1, H, accA, mapa(bar + 8 * (B_PE + wg), r ^ 1));
        }
        DBG(4);
        const uint32_t par = __shfl_sync(0xffffffffu, __float_as_uint(lds32f(sb + BAR_OFF + 504)), 0);
        uint32_t sl = sb + A_OFF + wg * A_WG + warp * 512 + lane * 16;
        uint4* gp = g_part + (size_t)(m * 8) * 1024 + wid * 128 + lane;
        asm volatile("" : "+r"(sl), "+l"(gp));
        const uint32_t pv = sl + f * 8192;
        auto settle = [&](int e, int b) {
#pragma unroll 1
            for (int it = 0; it < 1000000; it++) {
                asm volatile("cp.async.wait_all;" ::: "memory");
                uint32_t bad = 0;
#pragma unroll
                for (int d = 0; d < 4; d++) bad |= __float_as_uint(lds32f(pv + d * 2048)) ^ par;
                if (!__any_sync(0xffffffffu, bad & 1)) break;
#pragma unroll
                for (int d = 0; d < 4; d++) cp16(pv + d * 2048, gp + (e * 128 + b) * 1024 + d * 32);
            }
        };
        if (c.lead) mbar_arrive(bar + 8 * B_P1D);
#pragma unroll
        for (int j = 0; j < 32; j++) accB[j] = 0.f;
#pragma unroll 1
        for (int I = 1; I <= 4; I++) {
            const uint32_t la = sl + bufoff(I & 1, f);
            uint4* o = gp + ((I - 1) * 128 + ((f + 2 * I - 2) & 7)) * 1024;
            float4 v0 = make_float4(0.f, 0.f, 0.f, 0.f), v1 = v0;
            p2_issue<0, 0, true>(c, accB, H, I == 4);
            if (I > 1) {
                mbar_wait(bar + 8 * (B_PFULL + wg * 4 + I - 2), 0);
                v0 = lds128f(la); v1 = lds128f(la + 2048);
            }
            retire(c, 5);
            reg_fence(accA);
            sfor<0, 4>([&](auto dd) {
                constexpr int d = dd.v, k = 8 * d;
                p2_issue<0, 1 + d>(c, accB, H);
                const uint32_t x = pack_bf16(accA[k] + v0.x, accA[k + 1] + v0.y), y = pack_bf16(accA[k + 2] + v0.z, accA[k + 3] + v0.w);
                const uint32_t z = pack_bf16(accA[k + 4] + v1.x, accA[k + 5] + v1.y), w = pack_bf16(accA[k + 6] + v1.z, accA[k + 7] + v1.w);
                if (d < 3 && I > 1) { v0 = lds128f(la + (2 * d + 2) * 2048); v1 = lds128f(la + (2 * d + 3) * 2048); }
                st_tagged(o + d * 32, x, y, z, w, par);
                if constexpr (d == 3) { if (I > 2) settle(I - 2, (f + 2 * I) & 7); }
                retire(c, d);
            });
            p2_issue<0, 5>(c, accB, H);
            if (I > 2) {
#pragma unroll
                for (int d = 0; d < 4; d++) {
                    const uint4 v = lds128u(pv + d * 2048);
                    accA[8 * d] = bf_lo(v.x); accA[8 * d + 1] = bf_hi(v.x); accA[8 * d + 2] = bf_lo(v.y); accA[8 * d + 3] = bf_hi(v.y);
                    accA[8 * d + 4] = bf_lo(v.z); accA[8 * d + 5] = bf_hi(v.z); accA[8 * d + 6] = bf_lo(v.w); accA[8 * d + 7] = bf_hi(v.w);
                }
            }
            retire(c, 4);
            DBG(20);
            const uint4* q = gp + ((I - 1) * 128 + (I == 2 ? (f + 6) & 7 : f)) * 1024;
            p2_issue<1, 0, true>(c, accA, H, I > 2);
            if (I > 1) cp16(pv, q);
            if (I == 1) mbar_wait(bar + 8 * (B_PE + wg), 0);
            const uint32_t dst = mapa(sl + bufoff((I - 1) & 1, f), r ^ 1);
            const uint32_t pf = mapa(bar + 8 * (B_PFULL + wg * 4 + I - 1), r ^ 1);
            retire(c, 5);
            reg_fence(accB);
            sfor<0, 4>([&](auto dd) {
                constexpr int d = dd.v;
                p2_issue<1, 1 + d>(c, accA, H);
                if (d < 3 && I > 1) cp16(pv + (d + 1) * 2048, q + (d + 1) * 32);
#pragma unroll
                for (int j = (SFAST ? 3 * d : 2 * d); j < (SFAST ? (d < 2 ? 3 * d + 3 : 8) : 2 * d + 2); j++)
                    asm volatile("st.async.weak.shared::cluster.mbarrier::complete_tx::bytes.v4.f32 [%0], {%1,%2,%3,%4}, [%5];"
                                 ::"r"(dst + j * 2048), "f"(accB[4 * j]), "f"(accB[4 * j + 1]), "f"(accB[4 * j + 2]), "f"(accB[4 * j + 3]), "r"(pf) : "memory");
                if constexpr (d < 3) retire(c, d);
            });
            if (I == 4) break;
            if (I == 1 && c.lead) mbar_arrive(bar + 8 * B_TICK);
            retire(c, 3);
            p2_issue<1, 5>(c, accA, H);
            if (I == 3) {
                mbar_wait(bar + 8 * B_Z, 0);
#pragma unroll
                for (int j = 0; j < 8; j++) {
                    const float4 v = lds128f(sl + bufoff(2, f) + j * 2048);
                    accB[4 * j] = v.x; accB[4 * j + 1] = v.y; accB[4 * j + 2] = v.z; accB[4 * j + 3] = v.w;
                }
            }
            retire(c, 4);
            DBG(4 + I);
        }
        DBG(23);
        p2_issue<1, 5>(c, accA, H);
        DBG(22);
        const float r0 = 0.5f * lds32f(sb + RS_OFF + (wid * 16 + (lane >> 2)) * 4), r1 = 0.5f * lds32f(sb + RS_OFF + (wid * 16 + 8 + (lane >> 2)) * 4);
        const uint32_t yb = sl + bufoff(2, f);
        settle(3, f);
        DBG(24);
        mbar_wait(bar + 8 * (B_PFULL + wg * 4 + 3), 0);
        DBG(25);
#pragma unroll
        for (int d = 0; d < 4; d++) {
            const uint4 v = lds128u(pv + d * 2048);
            const float4 v0 = lds128f(sl + bufoff(1, f) + d * 4096), v1 = lds128f(sl + bufoff(1, f) + d * 4096 + 2048);
            accB[8 * d] = (bf_lo(v.x) + v0.x) * r0; accB[8 * d + 1] = (bf_hi(v.x) + v0.y) * r0; accB[8 * d + 2] = (bf_lo(v.y) + v0.z) * r1; accB[8 * d + 3] = (bf_hi(v.y) + v0.w) * r1;
            accB[8 * d + 4] = (bf_lo(v.z) + v1.x) * r0; accB[8 * d + 5] = (bf_hi(v.z) + v1.y) * r0; accB[8 * d + 6] = (bf_lo(v.w) + v1.z) * r1; accB[8 * d + 7] = (bf_hi(v.w) + v1.w) * r1;
        }
        DBG(8);
        wg_wait<0>();
        reg_fence(accA);
        DBG(9);
        const uint32_t stg = yb - lane * 16;
        __syncwarp();
#pragma unroll
        for (int j = 0; j < 8; j += 2) {
            const int mi = lane >> 3, rr = (lane & 7) + (mi & 1) * 8;
            const uint32_t a = stg + (rr >> 2) * 2048 + (rr & 3) * 128 + (((j + (mi >> 1)) ^ (rr & 7)) << 4);
            uint32_t q[4];
#pragma unroll
            for (int i = 0; i < 4; i++) {
                const int e = 4 * j + 2 * i;
                const float rs = (i & 1) ? r1 : r0;
                q[i] = pack_bf16(fmaf(accA[e], rs, accB[e]), fmaf(accA[e + 1], rs, accB[e + 1]));
            }
            asm volatile("stmatrix.sync.aligned.m8n8.x4.shared.b16 [%0], {%1,%2,%3,%4};" ::"r"(a), "r"(q[0]), "r"(q[1]), "r"(q[2]), "r"(q[3]) : "memory");
        }
        __syncwarp();
#pragma unroll
        for (int i = 0; i < 4; i++) {
            const int rr = i * 4 + (lane >> 3), ch = lane & 7;
            const uint4 v = lds128u(stg + i * 2048 + (lane >> 3) * 128 + ((ch ^ (rr & 7)) << 4));
            *(uint4*)(out + (size_t)(m * 128 + wid * 16 + rr) * D_ + f * 64 + ch * 8) = v;
        }
        DBG(10);
    }
}
}

namespace cv {
constexpr int KV_UNIT = 12800, V_REL = 7040;
constexpr int KV_OFF = 0;
constexpr int XS_OFF = 51200;
constexpr int W_OFF = 71680, W_PITCH = 8448;
constexpr int K_OFF = 113920, K_PITCH = 4368;
constexpr int XT_OFF = 135808;
constexpr int Z_OFF = 156288, Z_ARR = 4224, Z_SET = 4 * Z_ARR;
constexpr int MR_OFF = 190080;
constexpr int CF_OFF = 198272;
constexpr int BAR_OFF = 198656;
constexpr int SMEM = 199168;
static_assert(3 * Z_SET <= XS_OFF, "");
constexpr int B_LD = 0, B_LX = 4, B_KF = 5, B_UF = 7, B_UF2 = 11, B_XF = 12, B_ST = 13, B_KVD = 14, B_ZF = 15, B_N = 25;

__device__ __forceinline__ uint32_t hmul2(uint32_t a, uint32_t b) { uint32_t r; asm("mul.rn.bf16x2 %0, %1, %2;" : "=r"(r) : "r"(a), "r"(b)); return r; }
__device__ __forceinline__ uint32_t hadd2(uint32_t a, uint32_t b) { uint32_t r; asm("add.rn.bf16x2 %0, %1, %2;" : "=r"(r) : "r"(a), "r"(b)); return r; }
__device__ __forceinline__ uint32_t hsub2(uint32_t a, uint32_t b) { uint32_t r; asm("sub.rn.bf16x2 %0, %1, %2;" : "=r"(r) : "r"(a), "r"(b)); return r; }
__device__ __forceinline__ uint32_t hfma2(uint32_t a, uint32_t b, uint32_t c) { uint32_t r; asm("fma.rn.bf16x2 %0, %1, %2, %3;" : "=r"(r) : "r"(a), "r"(b), "r"(c)); return r; }
__device__ __forceinline__ void ldsm4t(uint32_t* r, uint32_t a) {
    asm volatile("ldmatrix.sync.aligned.m8n8.x4.trans.shared.b16 {%0,%1,%2,%3}, [%4];" : "=r"(r[0]), "=r"(r[1]), "=r"(r[2]), "=r"(r[3]) : "r"(a));
}
__device__ __forceinline__ void stas4(uint32_t a, uint32_t x, uint32_t y, uint32_t z, uint32_t w, uint32_t mb) {
    asm volatile("st.async.weak.shared::cluster.mbarrier::complete_tx::bytes.v4.b32 [%0], {%1,%2,%3,%4}, [%5];" ::"r"(a), "r"(x), "r"(y), "r"(z), "r"(w), "r"(mb) : "memory");
}
__device__ __forceinline__ int wpos(int x) { const int j = (x >> 2) & 3, t = (x >> 4) & 3; return ((x & ~63) + 16 * j + 4 * (t ^ (j & 2)) + (x & 3)) * 4; }
__device__ __forceinline__ uint32_t zbase(uint32_t sb, int slot) { return sb + (slot < 2 ? Z_OFF + slot * Z_SET : KV_OFF + (slot - 2) * Z_SET); }

__device__ __forceinline__ void kv_item(uint32_t sb, int c, int j, int rank, int lane) {
    const uint32_t bar = sb + BAR_OFF;
    const int g = lane >> 2, t = lane & 3;
    const uint32_t la = sb + KV_OFF + c * KV_UNIT + j * 16 + (((~lane & 1) << 2) + ((lane >> 1) & 3)) * 80 + (lane >> 3) * 640;
    uint32_t cw0, cw1;
    mbar_wait(bar + 8 * B_LD, 0);
    asm volatile("ld.shared.v2.b32 {%0,%1}, [%2];" : "=r"(cw0), "=r"(cw1) : "r"(sb + CF_OFF + (j * 8 + g) * 8));
    const uint32_t c0 = __byte_perm(cw0, 0, 0x1010), c1 = __byte_perm(cw0, 0, 0x3232), c2 = __byte_perm(cw1, 0, 0x1010), c3 = __byte_perm(cw1, 0, 0x3232);
    mbar_wait(bar + 8 * (B_LD + c), 0);
    uint32_t kp[12], vp[12];
    ldsm4t(kp, la); ldsm4t(kp + 4, la + 2560); ldsm4t(kp + 8, la + 5120);
    ldsm4t(vp, la + V_REL); ldsm4t(vp + 4, la + V_REL + 2560);
    asm volatile("ldmatrix.sync.aligned.m8n8.x1.trans.shared.b16 {%0}, [%1];" : "=r"(vp[8]) : "r"(la + V_REL + 5120));
    uint32_t u[9];
    uint32_t ksp = __byte_perm(kp[1], kp[0], 0x5432);
#pragma unroll
    for (int i = 0; i < 9; i++) {
        const uint32_t ks = __byte_perm(kp[i + 2], kp[i + 1], 0x5432);
        u[i] = hmul2(hfma2(c0, kp[i + 2], hfma2(c1, ks, hfma2(c2, kp[i + 1], hmul2(c3, ksp)))), vp[i]);
        ksp = ks;
    }
    const uint32_t dst = mapa(sb + W_OFF + j * W_PITCH + 256 + (c * 8 + rank) * 256, g);
    const uint32_t mb = mapa(bar + 8 * (j < 2 ? B_UF + c : B_UF2), g);
#pragma unroll
    for (int i = 0; i < 4; i++)
        stas4(dst + i * 64 + ((t ^ (i & 2)) << 4), __byte_perm(u[2 * i + 1], u[2 * i], 0x5432), u[2 * i + 1], __byte_perm(u[2 * i + 2], u[2 * i + 1], 0x5432), u[2 * i + 2], mb);
}
__device__ __forceinline__ void x_item(uint32_t sb, int c, int j, int rank, int lane) {
    const int g = lane >> 2, t = lane & 3;
    const uint32_t la = sb + XS_OFF + c * 5120 + j * 16 + (((lane & 1) << 2) + ((lane >> 1) & 3)) * 80 + (lane >> 3) * 640;
    uint32_t x[8];
    ldsm4t(x, la); ldsm4t(x + 4, la + 2560);
    const uint32_t dst = mapa(sb + XT_OFF + j * 4096 + (c * 8 + rank) * 128 + t * 16, g);
    const uint32_t mb = mapa(sb + BAR_OFF + 8 * B_XF, g);
    stas4(dst, x[0], x[1], x[2], x[3], mb);
    stas4(dst + 64, x[4], x[5], x[6], x[7], mb);
}
__device__ __forceinline__ void epi(uint32_t sb, int slot, int half, int ch, int tid) {
    const int b = half * 128 + tid;
    const uint32_t za = zbase(sb, slot) + b * 16;
    const uint4 x = lds128u(sb + XT_OFF + slot * 4096 + (b & ~7) * 16 + (b & 1) * 64 + ((b >> 1) & 3) * 16);
    uint4 q = lds128u(sb + MR_OFF + b * 16);
    const uint4 rs = lds128u(sb + MR_OFF + 4096 + b * 16);
    q.x = hmul2(hsub2(x.x, q.x), rs.x); q.y = hmul2(hsub2(x.y, q.y), rs.y); q.z = hmul2(hsub2(x.z, q.z), rs.z); q.w = hmul2(hsub2(x.w, q.w), rs.w);
    mbar_wait(sb + BAR_OFF + 8 * (B_ZF + slot * 2 + half), 0);
    uint4 z0 = lds128u(za), z1 = lds128u(za + Z_ARR), z2 = lds128u(za + 2 * Z_ARR);
    z0.x = hadd2(z0.x, z1.x); z0.y = hadd2(z0.y, z1.y); z0.z = hadd2(z0.z, z1.z); z0.w = hadd2(z0.w, z1.w);
    z1 = lds128u(za + 3 * Z_ARR);
    uint4 h;
    h.x = hfma2(q.x, hadd2(z0.x, hadd2(z2.x, z1.x)), x.x);
    h.y = hfma2(q.y, hadd2(z0.y, hadd2(z2.y, z1.y)), x.y);
    h.z = hfma2(q.z, hadd2(z0.z, hadd2(z2.z, z1.z)), x.z);
    h.w = hfma2(q.w, hadd2(z0.w, hadd2(z2.w, z1.w)), x.w);
    *(uint4*)(g_hT + (size_t)ch * S_ + b * 8) = h;
}

template <int P>
__device__ __forceinline__ void load_a(uint32_t (&a)[8], uint32_t w0, uint32_t w8) {
#pragma unroll
    for (int i = 0; i < 2; i++) {
        a[4 * i] = lds32u(w8 + (2 * P + i) * 512); a[4 * i + 1] = lds32u(w8 + (2 * P + i) * 512 + 256);
        a[4 * i + 2] = lds32u(w0 + (2 * P + i) * 512); a[4 * i + 3] = lds32u(w0 + (2 * P + i) * 512 + 256);
    }
}
template <int P, int OFF, int NA>
__device__ __forceinline__ void retire_cols(float (&acc)[NA], float& c0, float& c1, uint32_t za) {
    uint32_t q[4];
#pragma unroll
    for (int i = 0; i < 4; i++) {
        const int k = OFF + 4 * i;
        asm volatile("" : "+f"(acc[k]), "+f"(acc[k + 1]), "+f"(acc[k + 2]), "+f"(acc[k + 3])::"memory");
        q[i] = pack_bf16(acc[k] + c0, acc[k + 1] + c1);
        c0 = acc[k + 2]; c1 = acc[k + 3];
    }
    asm volatile("stmatrix.sync.aligned.m8n8.x4.trans.shared.b16 [%0], {%1,%2,%3,%4};" ::"r"(za + P * 512), "r"(q[0]), "r"(q[1]), "r"(q[2]), "r"(q[3]) : "memory");
}
template <int P, int C0, int N, int OFF, int SD, int NA>
__device__ __forceinline__ void pair_mma(float (&acc)[NA], const uint32_t (&a)[8], uint32_t kd) {
    WGrs<N>::template mma<OFF, 0, dlo(SM0 + K_OFF + 256 + 16 * (C0 - 32 * P), 16), dhi(128, 0), SD>(acc, a[0], a[1], a[2], a[3], kd);
    WGrs<N>::template mma<OFF, 0, dlo(SM0 + K_OFF + 16 * (C0 - 32 * P), 16), dhi(128, 0), 1>(acc, a[4], a[5], a[6], a[7], kd);
}
__device__ __forceinline__ void conv_slot(uint32_t sb, int slot, int wg, int warp, int lane, float dval) {
    const uint32_t bar = sb + BAR_OFF;
    const int o = 16 * warp + (lane >> 2) - 2 * (lane & 3);
    const uint32_t wb = sb + W_OFF + slot * W_PITCH + 256;
    const uint32_t w0 = wb + wpos(o), w8 = wb + wpos(o + 8);
    const uint32_t za = zbase(sb, slot) + warp * (Z_ARR + 32) + lane * 16;
    const uint32_t kd = slot * (K_PITCH >> 4);
    if (warp == 1 && lane < 16) sts128u(wb - 256 + lane * 16, 0, 0, 0, 0);
    if (warp == 2 && lane < 17) { sts128u(sb + K_OFF + slot * K_PITCH + lane * 16, 0, 0, 0, 0); fence_async_smem(); }
    mbar_wait(bar + 8 * (B_KF + (slot >= 2)), 0);
    if (slot >= 2) mbar_wait(bar + 8 * B_KVD, 0);
    if (lane < 2 * warp) asm volatile("st.shared.v4.b32 [%0], {%1,%1,%1,%1};" ::"r"(za - warp * 32), "r"(0) : "memory");
    if (warp == 0 && lane == 0) {
        const uint32_t ka = sb + K_OFF + slot * K_PITCH + 272, k01 = lds32u(ka);
        asm volatile("st.shared.b32 [%0], %1;" ::"r"(ka), "r"((pack_bf16(bf_lo(k01) + dval, 0.f) & 0xffffu) | (k01 & 0xffff0000u)) : "memory");
        fence_async_smem();
    }
    asm volatile("bar.sync %0, 128;" ::"r"(1 + wg) : "memory");
    float accT[16], accE[48], accL[64], c0 = 0.f, c1 = 0.f;
    uint32_t a[2][8];
    mbar_wait(bar + 8 * (slot < 2 ? B_UF : B_UF2), 0);
    DBG(slot < 2 ? 2 : 5);
    load_a<0>(a[0], w0, w8);
    sfor<0, 8>([&](auto pp) {
        constexpr int p = pp.v;
        if constexpr (p == 1) retire_cols<0, 0>(accT, c0, c1, za);
        if constexpr (p == 2 || p == 3) {
#pragma unroll
            for (int i = 16 * (p - 1); i < 48; i++) { float y; asm volatile("mov.b32 %0, %1;" : "=f"(y) : "f"(accE[i]) : "memory"); accE[i] = y; }
        }
        if constexpr (p > 4) {
#pragma unroll
            for (int i = 16 * (p - 4); i < 64; i++) { float y; asm volatile("mov.b32 %0, %1;" : "=f"(y) : "f"(accL[i]) : "memory"); accL[i] = y; }
        }
        wg_fence();
        if constexpr (p == 0) pair_mma<0, 0, 32, 0, 0>(accT, a[0], kd);
        if constexpr (p == 1) pair_mma<0, 32, 96, 0, 0>(accE, a[0], kd);
        if constexpr (p >= 1 && p < 4) pair_mma<p, 32 * p, 128 - 32 * p, 16 * (p - 1), 1>(accE, a[p & 1], kd);
        if constexpr (p < 4) pair_mma<p, 128, 128, 0, p != 0>(accL, a[p & 1], kd);
        else pair_mma<p, 32 * p, 256 - 32 * p, 16 * (p - 4), 1>(accL, a[p & 1], kd);
        wg_commit();
        if constexpr (p >= 2 && p <= 4) retire_cols<p - 1, 16 * (p - 2)>(accE, c0, c1, za);
        if constexpr (p > 4) retire_cols<p - 1, 16 * (p - 5)>(accL, c0, c1, za);
        if constexpr (p == 4) { __syncwarp(); if (lane == 0) mbar_arrive(bar + 8 * (B_ZF + slot * 2)); }
        if constexpr (p & 1 && p < 7) mbar_wait(bar + 8 * (slot < 2 ? B_UF + (p + 1) / 2 : B_UF2), 0);
        if constexpr (p < 7 && p != 1) load_a<p + 1>(a[(p + 1) & 1], w0, w8);
        wg_wait<0>();
        if constexpr (p == 1) load_a<2>(a[0], w0, w8);
        if constexpr (p == 3) DBG(slot < 2 ? 3 : 6);
    });
    retire_cols<7, 48>(accL, c0, c1, za);
    __syncwarp();
    if (lane == 0) mbar_arrive(bar + 8 * (B_ZF + slot * 2 + 1));
    DBG(slot < 2 ? 4 : 7);
}

__global__ void __launch_bounds__(512, 1) __cluster_dims__(8, 1, 1)
conv_kernel(const __grid_constant__ CUtensorMap mK, const __grid_constant__ CUtensorMap mKh, const __grid_constant__ CUtensorMap mV,
            const __grid_constant__ CUtensorMap mVh, const __grid_constant__ CUtensorMap mX, const bf16* __restrict__ x,
            const bf16* __restrict__ sk, const bf16* __restrict__ filt, const bf16* __restrict__ Dv) {
    extern __shared__ __align__(1024) unsigned char smem_raw[];
    const uint32_t sb = s2u(smem_raw);
    if ((sb & 0xFFFFFF) != SM0) __trap();
    const uint32_t bar = sb + BAR_OFF;
    const int wid = __shfl_sync(0xffffffffu, threadIdx.x >> 5, 0);
    const int lane = threadIdx.x & 31, wg = wid >> 2, warp = wid & 3;
    const int cl = blockIdx.x >> 3, rank = blockIdx.x & 7, c0 = cl * 40;
    const int ns = cl == 14 ? 2 : 5;
    DBG(0);
    if (elect_one()) {
        if (wid >= 12) {
            const int c = wid - 12, run = c * 32 + rank * 4;
            const uint32_t b = bar + 8 * (B_LD + c), d = sb + KV_OFF + c * KV_UNIT;
            mbar_init(b, 1);
            fence_async_smem();
            if (c > 0 && LDLAG) __nanosleep(c * LDLAG);
            tma3d(d + 1920, &mK, c0, run, 0, b);
            tma3d(d + V_REL + 640, &mV, c0, run, 0, b);
            tma3d(d, &mKh, c0, run - 1, 10, b);
            tma3d(d + V_REL, &mVh, c0, run - 1, 14, b);
            if (c == 0) bulk_g2s(sb + CF_OFF, sk + c0 * 4, ns * 64, b);
            mbar_expect(b, c == 0 ? KV_UNIT + ns * 64 : KV_UNIT);
        } else if (wid == 11) {
            mbar_init(bar + 8 * B_KF, 1);
            fence_async_smem();
            for (int j = 0; j < 2; j++) bulk_g2s(sb + K_OFF + j * K_PITCH + 272, filt + (size_t)(c0 + 8 * j + rank) * S_, 4096, bar + 8 * B_KF);
            mbar_expect(bar + 8 * B_KF, 8192);
        } else if (wid < 10) {
#pragma unroll 1
            for (int i = 0; i < 2; i++) {
                const int k = wid * 2 + i, bi = k == 0 ? B_LX : k + 5;
                mbar_init(bar + 8 * bi, bi >= B_ZF ? 4 : bi == B_KVD ? 8 : bi == B_ST ? 4 : 1);
                if (bi >= B_UF && bi <= B_XF) mbar_expect(bar + 8 * bi, bi < B_UF2 ? 4096 : bi == B_UF2 ? (ns - 2) * 8192 : ns * 4096);
            }
        } else {
            asm volatile("prefetch.tensormap [%0];" ::"l"(&mX) : "memory");
            asm volatile("griddepcontrol.launch_dependents;" ::: "memory");
        }
        asm volatile("fence.mbarrier_init.release.cluster;" ::: "memory");
    }
    __syncwarp();
    asm volatile("barrier.cluster.arrive.relaxed.aligned;" ::: "memory");
    const unsigned ep = __ldcg(&g_epoch1) + 1;
    float dval = 0.f, dval2 = 0.f;
    if (wg < 3) {
        if (wg < ns) dval = __bfloat162float(Dv[c0 + 8 * wg + rank]);
        if (wg + 3 < ns) dval2 = __bfloat162float(Dv[c0 + 8 * (wg + 3) + rank]);
    }
    asm volatile("barrier.cluster.wait.aligned;" ::: "memory");
    DBG(1);

    if (wg >= 2) {
        asm volatile("setmaxnreg.dec.sync.aligned.u32 96;");
        const int pw = wid - 8;
        if (pw == 7 && elect_one()) {
            mbar_wait(bar + 8 * (B_LD + XLAG), 0);
            mbar_expect(bar + 8 * (B_KF + 1), (ns - 2) * 4096);
            for (int j = 2; j < ns; j++) bulk_g2s(sb + K_OFF + j * K_PITCH + 272, filt + (size_t)(c0 + 8 * j + rank) * S_, 4096, bar + 8 * (B_KF + 1));
            mbar_expect(bar + 8 * B_LX, 20480);
            for (int c = 0; c < 4; c++) tma3d(sb + XS_OFF + c * 5120, &mX, c0, c * 32 + rank * 4, 0, bar + 8 * B_LX);
        }
        __syncwarp();
        const bool dost = ns == 2 || pw >= 4;
        const int row = (ns == 2 ? 1792 + rank * 32 + pw * 4 : blockIdx.x * 16 + (pw - 4) * 4) + (lane >> 3);
        uint4 v[9];
#pragma unroll 1
        for (int i = pw; i < 4 * ns; i += 8) {
            const int c = i / ns;
            if (dost && i + 8 >= 4 * ns) {
                mbar_wait(bar + 8 * (B_LD + XLAG), 0);
#pragma unroll
                for (int k = 0; k < 9; k++) v[k] = __ldg((const uint4*)(x + (size_t)row * D_) + k * 8 + (lane & 7));
            }
            kv_item(sb, c, i - c * ns, rank, lane);
        }
        __syncwarp();
        if (lane == 0) mbar_arrive(bar + 8 * B_KVD);
        DBG(10);
        if (dost) {
            float s = 0.f;
#pragma unroll
            for (int k = 0; k < 9; k++)
                s += ((bf_lo(v[k].x) + bf_hi(v[k].x)) + (bf_lo(v[k].y) + bf_hi(v[k].y))) + ((bf_lo(v[k].z) + bf_hi(v[k].z)) + (bf_lo(v[k].w) + bf_hi(v[k].w)));
            s += __shfl_xor_sync(0xffffffffu, s, 1); s += __shfl_xor_sync(0xffffffffu, s, 2); s += __shfl_xor_sync(0xffffffffu, s, 4);
            const float mean = s * (1.f / D_);
            float q0 = 0.f, q1 = 0.f;
#pragma unroll
            for (int k = 0; k < 9; k++) {
                const uint32_t w[4] = {v[k].x, v[k].y, v[k].z, v[k].w};
#pragma unroll
                for (int e = 0; e < 4; e++) { const float a = bf_lo(w[e]) - mean, b = bf_hi(w[e]) - mean; q0 = fmaf(a, a, q0); q1 = fmaf(b, b, q1); }
            }
            q0 += q1;
            q0 += __shfl_xor_sync(0xffffffffu, q0, 1); q0 += __shfl_xor_sync(0xffffffffu, q0, 2); q0 += __shfl_xor_sync(0xffffffffu, q0, 4);
            const uint32_t o = (pack_bf16(mean, rsqrtf(q0 * (1.f / D_) + 1e-5f)) & 0x7fffffffu) | (ep << 31);
            if ((lane & 7) == 0) asm volatile("st.relaxed.gpu.global.u32 [%0], %1;" ::"l"(g_st1 + row), "r"(o) : "memory");
        }
        DBG(8);
    }
    if (wg < 3) {
        asm volatile("setmaxnreg.inc.sync.aligned.u32 160;");
        const int tid = threadIdx.x & 127;
#pragma unroll 1
        for (int slot = wg; slot < ns; slot += 3) {
            conv_slot(sb, slot, wg, warp, lane, slot < 3 ? dval : dval2);
            if (slot + 3 >= ns) {
                mbar_wait(bar + 8 * B_XF, 0);
                mbar_wait(bar + 8 * B_ST, 0);
                epi(sb, slot, 1, c0 + 8 * slot + rank, tid);
            }
        }
        DBG(9);
    } else {
        asm volatile("setmaxnreg.dec.sync.aligned.u32 32;");
        const int tid = threadIdx.x & 127;
        mbar_wait(bar + 8 * B_LX, 0);
#pragma unroll 1
        for (int i = warp; i < 4 * ns; i += 4) x_item(sb, i & 3, i >> 2, rank, lane);
        DBG(11);
#pragma unroll 1
        for (int hf = 0; hf < 2; hf++) {
            const uint32_t* p = g_st1 + (hf * 128 + tid) * 8;
            uint4 v0, v1;
            for (int it = 0; it < 1000000; it++) {
                asm volatile("ld.relaxed.gpu.global.v4.b32 {%0,%1,%2,%3}, [%4];" : "=r"(v0.x), "=r"(v0.y), "=r"(v0.z), "=r"(v0.w) : "l"(p) : "memory");
                asm volatile("ld.relaxed.gpu.global.v4.b32 {%0,%1,%2,%3}, [%4];" : "=r"(v1.x), "=r"(v1.y), "=r"(v1.z), "=r"(v1.w) : "l"(p + 4) : "memory");
                const uint32_t e = ep << 31;
                if (!(((v0.x ^ e) | (v0.y ^ e) | (v0.z ^ e) | (v0.w ^ e) | (v1.x ^ e) | (v1.y ^ e) | (v1.z ^ e) | (v1.w ^ e)) >> 31)) break;
            }
            const uint32_t a = sb + MR_OFF + (hf * 128 + tid) * 16;
            asm volatile("st.shared.v4.b32 [%0], {%1,%2,%3,%4};" ::"r"(a), "r"(__byte_perm(v0.x, v0.y, 0x5410)), "r"(__byte_perm(v0.z, v0.w, 0x5410)),
                         "r"(__byte_perm(v1.x, v1.y, 0x5410)), "r"(__byte_perm(v1.z, v1.w, 0x5410)) : "memory");
            asm volatile("st.shared.v4.b32 [%0], {%1,%2,%3,%4};" ::"r"(a + 4096), "r"(__byte_perm(v0.x, v0.y, 0x7632) & 0x7fff7fffu), "r"(__byte_perm(v0.z, v0.w, 0x7632) & 0x7fff7fffu),
                         "r"(__byte_perm(v1.x, v1.y, 0x7632) & 0x7fff7fffu), "r"(__byte_perm(v1.z, v1.w, 0x7632) & 0x7fff7fffu) : "memory");
        }
        __syncwarp();
        if (lane == 0) mbar_arrive(bar + 8 * B_ST);
        if (blockIdx.x == 0 && tid == 0) g_epoch = ep;
        DBG(12);
        mbar_wait(bar + 8 * B_XF, 0);
        DBG(13);
#pragma unroll 1
        for (int i = 0; i < (ns == 5 ? 7 : 2); i++) {
            const int slot = i < 4 ? i & 1 : i - 2, half = (i >> 1) == 1;
            epi(sb, slot, half, c0 + 8 * slot + rank, tid);
        }
        DBG(9);
    }
}
}

typedef CUresult (*EncFn)(CUtensorMap*, CUtensorMapDataType, cuuint32_t, void*, const cuuint64_t*, const cuuint64_t*, const cuuint32_t*,
                          const cuuint32_t*, CUtensorMapInterleave, CUtensorMapSwizzle, CUtensorMapL2promotion, CUtensorMapFloatOOBfill);
static void enc(EncFn fn, CUtensorMap* m, int rank, const void* base, const cuuint64_t* dims, const cuuint64_t* strides, const cuuint32_t* box, CUtensorMapSwizzle sw) {
    cuuint32_t es[5] = {1, 1, 1, 1, 1};
    fn(m, CU_TENSOR_MAP_DATA_TYPE_BFLOAT16, rank, (void*)base, dims, strides, box, es, CU_TENSOR_MAP_INTERLEAVE_NONE, sw,
       CU_TENSOR_MAP_L2_PROMOTION_L2_128B, CU_TENSOR_MAP_FLOAT_OOB_FILL_NONE);
}

extern "C" void kernel_launch(void* const* d_in, const int* in_sizes, int n_in, void* d_out, int out_size) {
    const bf16 *x = (const bf16*)d_in[0], *k = (const bf16*)d_in[1], *v = (const bf16*)d_in[2], *sk = (const bf16*)d_in[3],
               *K = (const bf16*)d_in[4], *Dv = (const bf16*)d_in[5], *w1 = (const bf16*)d_in[7], *b1 = (const bf16*)d_in[8],
               *w2 = (const bf16*)d_in[9], *b2 = (const bf16*)d_in[10];
    bf16* out = (bf16*)d_out;
    void* fp = nullptr; cudaDriverEntryPointQueryResult q;
    cudaGetDriverEntryPoint("cuTensorMapEncodeTiled", &fp, cudaEnableDefault, &q);
    EncFn fn = (EncFn)fp;
    void* hT; cudaGetSymbolAddress(&hT, g_hT);
    ffn::Maps mp;
    { cuuint64_t d[2] = {S_, D_}, s[1] = {S_ * 2}; cuuint32_t b[2] = {64, 64}; enc(fn, &mp.h, 2, hT, d, s, b, CU_TENSOR_MAP_SWIZZLE_128B); }
    { cuuint64_t d[3] = {32, D_, F_ / 32}, s[2] = {F_ * 2, 64}; cuuint32_t b[3] = {32, 64, 3}; enc(fn, &mp.w1[1], 3, w1, d, s, b, CU_TENSOR_MAP_SWIZZLE_64B); }
    { cuuint64_t d[3] = {64, D_, F_ / 64}, s[2] = {F_ * 2, 128};
      cuuint32_t b2_[3] = {64, 48, 2}; enc(fn, &mp.w1[2], 3, w1, d, s, b2_, CU_TENSOR_MAP_SWIZZLE_128B);
      cuuint32_t b3_[3] = {64, 96, 1}; enc(fn, &mp.w1[0], 3, w1, d, s, b3_, CU_TENSOR_MAP_SWIZZLE_128B); }
    { cuuint64_t d[2] = {D_, F_}, s[1] = {D_ * 2}; cuuint32_t b[2] = {64, 96}; enc(fn, &mp.w2, 2, w2, d, s, b, CU_TENSOR_MAP_SWIZZLE_128B); }
    CUtensorMap mK, mKh, mV, mVh, mX;
    { cuuint64_t d[3] = {D_, S_ / 16, 16}, s[2] = {16 * D_ * 2, D_ * 2};
      cuuint32_t bm[3] = {40, 4, 16}, bk[3] = {40, 4, 6}, bv[3] = {40, 4, 2};
      enc(fn, &mK, 3, k, d, s, bm, CU_TENSOR_MAP_SWIZZLE_NONE); enc(fn, &mKh, 3, k, d, s, bk, CU_TENSOR_MAP_SWIZZLE_NONE);
      enc(fn, &mV, 3, v, d, s, bm, CU_TENSOR_MAP_SWIZZLE_NONE); enc(fn, &mVh, 3, v, d, s, bv, CU_TENSOR_MAP_SWIZZLE_NONE);
      enc(fn, &mX, 3, x, d, s, bm, CU_TENSOR_MAP_SWIZZLE_NONE); }
    cudaFuncSetAttribute(ffn::ffn_kernel, cudaFuncAttributeMaxDynamicSharedMemorySize, ffn::SMEM);
    cudaFuncSetAttribute(cv::conv_kernel, cudaFuncAttributeMaxDynamicSharedMemorySize, cv::SMEM);
    cudaStream_t st = cudaStreamPerThread;
    cv::conv_kernel<<<120, 512, cv::SMEM, st>>>(mK, mKh, mV, mVh, mX, x, sk, K, Dv);
    cudaLaunchConfig_t cf = {};
    cf.gridDim = dim3(132); cf.blockDim = dim3(384); cf.dynamicSmemBytes = ffn::SMEM; cf.stream = st;
    cudaLaunchAttribute at[1];
    at[0].id = cudaLaunchAttributeProgrammaticStreamSerialization; at[0].val.programmaticStreamSerializationAllowed = 1;
    cf.attrs = at; cf.numAttrs = 1;
    cudaLaunchKernelEx(&cf, ffn::ffn_kernel, mp, b1, w2, b2, out);
}
```

```cpp
#include <cuda_runtime.h>
#include <cuda.h>
#include <cuda_bf16.h>
#include <stdint.h>

typedef __nv_bfloat16 bf16;
constexpr int S_ = 2048, D_ = 576, F_ = 4608;

template<int N> struct WGrs;
template<int N> struct WGss;
template<> struct WGrs<32> { template<int OFF,int TB,uint32_t BO,uint32_t BH,int SD,int NA> static __device__ __forceinline__ void mma(float (&d)[NA], uint32_t a0, uint32_t a1, uint32_t a2, uint32_t a3, uint32_t lb) {
  asm volatile("{.reg .pred p; .reg .b32 y; .reg .b64 db; setp.ne.b32 p, %21, 0; add.u32 y, %20, %23; mov.b64 db, {y, %24};\n"
   "wgmma.mma_async.sync.aligned.m64n32k16.f32.bf16.bf16 {%0, %1, %2, %3, %4, %5, %6, %7, %8, %9, %10, %11, %12, %13, %14, %15}, {%16, %17, %18, %19}, db, p, 1, 1, %22;}"
   : "+f"(d[OFF+0]), "+f"(d[OFF+1]), "+f"(d[OFF+2]), "+f"(d[OFF+3]), "+f"(d[OFF+4]), "+f"(d[OFF+5]), "+f"(d[OFF+6]), "+f"(d[OFF+7]), "+f"(d[OFF+8]), "+f"(d[OFF+9]), "+f"(d[OFF+10]), "+f"(d[OFF+11]), "+f"(d[OFF+12]), "+f"(d[OFF+13]), "+f"(d[OFF+14]), "+f"(d[OFF+15])
   : "r"(a0), "r"(a1), "r"(a2), "r"(a3), "r"(lb), "n"(SD), "n"(TB), "n"(BO), "n"(BH)); }
 template<int OFF,int TB,uint32_t BO,uint32_t BH,int NA> static __device__ __forceinline__ void mma_p(float (&d)[NA], uint32_t a0, uint32_t a1, uint32_t a2, uint32_t a3, uint32_t lb, int sd) {
  asm volatile("{.reg .pred p; .reg .b32 y; .reg .b64 db; setp.ne.b32 p, %21, 0; add.u32 y, %20, %23; mov.b64 db, {y, %24};\n"
   "wgmma.mma_async.sync.aligned.m64n32k16.f32.bf16.bf16 {%0, %1, %2, %3, %4, %5, %6, %7, %8, %9, %10, %11, %12, %13, %14, %15}, {%16, %17, %18, %19}, db, p, 1, 1, %22;}"
   : "+f"(d[OFF+0]), "+f"(d[OFF+1]), "+f"(d[OFF+2]), "+f"(d[OFF+3]), "+f"(d[OFF+4]), "+f"(d[OFF+5]), "+f"(d[OFF+6]), "+f"(d[OFF+7]), "+f"(d[OFF+8]), "+f"(d[OFF+9]), "+f"(d[OFF+10]), "+f"(d[OFF+11]), "+f"(d[OFF+12]), "+f"(d[OFF+13]), "+f"(d[OFF+14]), "+f"(d[OFF+15])
   : "r"(a0), "r"(a1), "r"(a2), "r"(a3), "r"(lb), "r"(sd), "n"(TB), "n"(BO), "n"(BH)); } };
template<> struct WGrs<64> { template<int OFF,int TB,uint32_t BO,uint32_t BH,int SD,int NA> static __device__ __forceinline__ void mma(float (&d)[NA], uint32_t a0, uint32_t a1, uint32_t a2, uint32_t a3, uint32_t lb) {
  asm volatile("{.reg .pred p; .reg .b32 y; .reg .b64 db; setp.ne.b32 p, %37, 0; add.u32 y, %36, %39; mov.b64 db, {y, %40};\n"
   "wgmma.mma_async.sync.aligned.m64n64k16.f32.bf16.bf16 {%0, %1, %2, %3, %4, %5, %6, %7, %8, %9, %10, %11, %12, %13, %14, %15, %16, %17, %18, %19, %20, %21, %22, %23, %24, %25, %26, %27, %28, %29, %30, %31}, {%32, %33, %34, %35}, db, p, 1, 1, %38;}"
   : "+f"(d[OFF+0]), "+f"(d[OFF+1]), "+f"(d[OFF+2]), "+f"(d[OFF+3]), "+f"(d[OFF+4]), "+f"(d[OFF+5]), "+f"(d[OFF+6]), "+f"(d[OFF+7]), "+f"(d[OFF+8]), "+f"(d[OFF+9]), "+f"(d[OFF+10]), "+f"(d[OFF+11]), "+f"(d[OFF+12]), "+f"(d[OFF+13]), "+f"(d[OFF+14]), "+f"(d[OFF+15]), "+f"(d[OFF+16]), "+f"(d[OFF+17]), "+f"(d[OFF+18]), "+f"(d[OFF+19]), "+f"(d[OFF+20]), "+f"(d[OFF+21]), "+f"(d[OFF+22]), "+f"(d[OFF+23]), "+f"(d[OFF+24]), "+f"(d[OFF+25]), "+f"(d[OFF+26]), "+f"(d[OFF+27]), "+f"(d[OFF+28]), "+f"(d[OFF+29]), "+f"(d[OFF+30]), "+f"(d[OFF+31])
   : "r"(a0), "r"(a1), "r"(a2), "r"(a3), "r"(lb), "n"(SD), "n"(TB), "n"(BO), "n"(BH)); }
 template<int OFF,int TB,uint32_t BO,uint32_t BH,int NA> static __device__ __forceinline__ void mma_p(float (&d)[NA], uint32_t a0, uint32_t a1, uint32_t a2, uint32_t a3, uint32_t lb, int sd) {
  asm volatile("{.reg .pred p; .reg .b32 y; .reg .b64 db; setp.ne.b32 p, %37, 0; add.u32 y, %36, %39; mov.b64 db, {y, %40};\n"
   "wgmma.mma_async.sync.aligned.m64n64k16.f32.bf16.bf16 {%0, %1, %2, %3, %4, %5, %6, %7, %8, %9, %10, %11, %12, %13, %14, %15, %16, %17, %18, %19, %20, %21, %22, %23, %24, %25, %26, %27, %28, %29, %30, %31}, {%32, %33, %34, %35}, db, p, 1, 1, %38;}"
   : "+f"(d[OFF+0]), "+f"(d[OFF+1]), "+f"(d[OFF+2]), "+f"(d[OFF+3]), "+f"(d[OFF+4]), "+f"(d[OFF+5]), "+f"(d[OFF+6]), "+f"(d[OFF+7]), "+f"(d[OFF+8]), "+f"(d[OFF+9]), "+f"(d[OFF+10]), "+f"(d[OFF+11]), "+f"(d[OFF+12]), "+f"(d[OFF+13]), "+f"(d[OFF+14]), "+f"(d[OFF+15]), "+f"(d[OFF+16]), "+f"(d[OFF+17]), "+f"(d[OFF+18]), "+f"(d[OFF+19]), "+f"(d[OFF+20]), "+f"(d[OFF+21]), "+f"(d[OFF+22]), "+f"(d[OFF+23]), "+f"(d[OFF+24]), "+f"(d[OFF+25]), "+f"(d[OFF+26]), "+f"(d[OFF+27]), "+f"(d[OFF+28]), "+f"(d[OFF+29]), "+f"(d[OFF+30]), "+f"(d[OFF+31])
   : "r"(a0), "r"(a1), "r"(a2), "r"(a3), "r"(lb), "r"(sd), "n"(TB), "n"(BO), "n"(BH)); } };
template<> struct WGrs<128> { template<int OFF,int TB,uint32_t BO,uint32_t BH,int SD,int NA> static __device__ __forceinline__ void mma(float (&d)[NA], uint32_t a0, uint32_t a1, uint32_t a2, uint32_t a3, uint32_t lb) {
  asm volatile("{.reg .pred p; .reg .b32 y; .reg .b64 db; setp.ne.b32 p, %69, 0; add.u32 y, %68, %71; mov.b64 db, {y, %72};\n"
   "wgmma.mma_async.sync.aligned.m64n128k16.f32.bf16.bf16 {%0, %1, %2, %3, %4, %5, %6, %7, %8, %9, %10, %11, %12, %13, %14, %15, %16, %17, %18, %19, %20, %21, %22, %23, %24, %25, %26, %27, %28, %29, %30, %31, %32, %33, %34, %35, %36, %37, %38, %39, %40, %41, %42, %43, %44, %45, %46, %47, %48, %49, %50, %51, %52, %53, %54, %55, %56, %57, %58, %59, %60, %61, %62, %63}, {%64, %65, %66, %67}, db, p, 1, 1, %70;}"
   : "+f"(d[OFF+0]), "+f"(d[OFF+1]), "+f"(d[OFF+2]), "+f"(d[OFF+3]), "+f"(d[OFF+4]), "+f"(d[OFF+5]), "+f"(d[OFF+6]), "+f"(d[OFF+7]), "+f"(d[OFF+8]), "+f"(d[OFF+9]), "+f"(d[OFF+10]), "+f"(d[OFF+11]), "+f"(d[OFF+12]), "+f"(d[OFF+13]), "+f"(d[OFF+14]), "+f"(d[OFF+15]), "+f"(d[OFF+16]), "+f"(d[OFF+17]), "+f"(d[OFF+18]), "+f"(d[OFF+19]), "+f"(d[OFF+20]), "+f"(d[OFF+21]), "+f"(d[OFF+22]), "+f"(d[OFF+23]), "+f"(d[OFF+24]), "+f"(d[OFF+25]), "+f"(d[OFF+26]), "+f"(d[OFF+27]), "+f"(d[OFF+28]), "+f"(d[OFF+29]), "+f"(d[OFF+30]), "+f"(d[OFF+31]), "+f"(d[OFF+32]), "+f"(d[OFF+33]), "+f"(d[OFF+34]), "+f"(d[OFF+35]), "+f"(d[OFF+36]), "+f"(d[OFF+37]), "+f"(d[OFF+38]), "+f"(d[OFF+39]), "+f"(d[OFF+40]), "+f"(d[OFF+41]), "+f"(d[OFF+42]), "+f"(d[OFF+43]), "+f"(d[OFF+44]), "+f"(d[OFF+45]), "+f"(d[OFF+46]), "+f"(d[OFF+47]), "+f"(d[OFF+48]), "+f"(d[OFF+49]), "+f"(d[OFF+50]), "+f"(d[OFF+51]), "+f"(d[OFF+52]), "+f"(d[OFF+53]), "+f"(d[OFF+54]), "+f"(d[OFF+55]), "+f"(d[OFF+56]), "+f"(d[OFF+57]), "+f"(d[OFF+58]), "+f"(d[OFF+59]), "+f"(d[OFF+60]), "+f"(d[OFF+61]), "+f"(d[OFF+62]), "+f"(d[OFF+63])
   : "r"(a0), "r"(a1), "r"(a2), "r"(a3), "r"(lb), "n"(SD), "n"(TB), "n"(BO), "n"(BH)); }
 template<int OFF,int TB,uint32_t BO,uint32_t BH,int NA> static __device__ __forceinline__ void mma_p(float (&d)[NA], uint32_t a0, uint32_t a1, uint32_t a2, uint32_t a3, uint32_t lb, int sd) {
  asm volatile("{.reg .pred p; .reg .b32 y; .reg .b64 db; setp.ne.b32 p, %69, 0; add.u32 y, %68, %71; mov.b64 db, {y, %72};\n"
   "wgmma.mma_async.sync.aligned.m64n128k16.f32.bf16.bf16 {%0, %1, %2, %3, %4, %5, %6, %7, %8, %9, %10, %11, %12, %13, %14, %15, %16, %17, %18, %19, %20, %21, %22, %23, %24, %25, %26, %27, %28, %29, %30, %31, %32, %33, %34, %35, %36, %37, %38, %39, %40, %41, %42, %43, %44, %45, %46, %47, %48, %49, %50, %51, %52, %53, %54, %55, %56, %57, %58, %59, %60, %61, %62, %63}, {%64, %65, %66, %67}, db, p, 1, 1, %70;}"
   : "+f"(d[OFF+0]), "+f"(d[OFF+1]), "+f"(d[OFF+2]), "+f"(d[OFF+3]), "+f"(d[OFF+4]), "+f"(d[OFF+5]), "+f"(d[OFF+6]), "+f"(d[OFF+7]), "+f"(d[OFF+8]), "+f"(d[OFF+9]), "+f"(d[OFF+10]), "+f"(d[OFF+11]), "+f"(d[OFF+12]), "+f"(d[OFF+13]), "+f"(d[OFF+14]), "+f"(d[OFF+15]), "+f"(d[OFF+16]), "+f"(d[OFF+17]), "+f"(d[OFF+18]), "+f"(d[OFF+19]), "+f"(d[OFF+20]), "+f"(d[OFF+21]), "+f"(d[OFF+22]), "+f"(d[OFF+23]), "+f"(d[OFF+24]), "+f"(d[OFF+25]), "+f"(d[OFF+26]), "+f"(d[OFF+27]), "+f"(d[OFF+28]), "+f"(d[OFF+29]), "+f"(d[OFF+30]), "+f"(d[OFF+31]), "+f"(d[OFF+32]), "+f"(d[OFF+33]), "+f"(d[OFF+34]), "+f"(d[OFF+35]), "+f"(d[OFF+36]), "+f"(d[OFF+37]), "+f"(d[OFF+38]), "+f"(d[OFF+39]), "+f"(d[OFF+40]), "+f"(d[OFF+41]), "+f"(d[OFF+42]), "+f"(d[OFF+43]), "+f"(d[OFF+44]), "+f"(d[OFF+45]), "+f"(d[OFF+46]), "+f"(d[OFF+47]), "+f"(d[OFF+48]), "+f"(d[OFF+49]), "+f"(d[OFF+50]), "+f"(d[OFF+51]), "+f"(d[OFF+52]), "+f"(d[OFF+53]), "+f"(d[OFF+54]), "+f"(d[OFF+55]), "+f"(d[OFF+56]), "+f"(d[OFF+57]), "+f"(d[OFF+58]), "+f"(d[OFF+59]), "+f"(d[OFF+60]), "+f"(d[OFF+61]), "+f"(d[OFF+62]), "+f"(d[OFF+63])
   : "r"(a0), "r"(a1), "r"(a2), "r"(a3), "r"(lb), "r"(sd), "n"(TB), "n"(BO), "n"(BH)); } };
template<> struct WGss<64> { template<int OFF,int TA,int TB,uint32_t AO,uint32_t AH,uint32_t BO,uint32_t BH,int SD,int NA> static __device__ __forceinline__ void mma(float (&d)[NA], uint32_t la, uint32_t lb) {
  asm volatile("{.reg .pred p; .reg .b32 x, y; .reg .b64 da, db; setp.ne.b32 p, %34, 0; add.u32 x, %32, %37; mov.b64 da, {x, %38}; add.u32 y, %33, %39; mov.b64 db, {y, %40};\n"
   "wgmma.mma_async.sync.aligned.m64n64k16.f32.bf16.bf16 {%0, %1, %2, %3, %4, %5, %6, %7, %8, %9, %10, %11, %12, %13, %14, %15, %16, %17, %18, %19, %20, %21, %22, %23, %24, %25, %26, %27, %28, %29, %30, %31}, da, db, p, 1, 1, %35, %36;}"
   : "+f"(d[OFF+0]), "+f"(d[OFF+1]), "+f"(d[OFF+2]), "+f"(d[OFF+3]), "+f"(d[OFF+4]), "+f"(d[OFF+5]), "+f"(d[OFF+6]), "+f"(d[OFF+7]), "+f"(d[OFF+8]), "+f"(d[OFF+9]), "+f"(d[OFF+10]), "+f"(d[OFF+11]), "+f"(d[OFF+12]), "+f"(d[OFF+13]), "+f"(d[OFF+14]), "+f"(d[OFF+15]), "+f"(d[OFF+16]), "+f"(d[OFF+17]), "+f"(d[OFF+18]), "+f"(d[OFF+19]), "+f"(d[OFF+20]), "+f"(d[OFF+21]), "+f"(d[OFF+22]), "+f"(d[OFF+23]), "+f"(d[OFF+24]), "+f"(d[OFF+25]), "+f"(d[OFF+26]), "+f"(d[OFF+27]), "+f"(d[OFF+28]), "+f"(d[OFF+29]), "+f"(d[OFF+30]), "+f"(d[OFF+31])
   : "r"(la), "r"(lb), "n"(SD), "n"(TA), "n"(TB), "n"(AO), "n"(AH), "n"(BO), "n"(BH)); } };
template<> struct WGss<96> { template<int OFF,int TA,int TB,uint32_t AO,uint32_t AH,uint32_t BO,uint32_t BH,int SD,int NA> static __device__ __forceinline__ void mma(float (&d)[NA], uint32_t la, uint32_t lb) {
  asm volatile("{.reg .pred p; .reg .b32 x, y; .reg .b64 da, db; setp.ne.b32 p, %50, 0; add.u32 x, %48, %53; mov.b64 da, {x, %54}; add.u32 y, %49, %55; mov.b64 db, {y, %56};\n"
   "wgmma.mma_async.sync.aligned.m64n96k16.f32.bf16.bf16 {%0, %1, %2, %3, %4, %5, %6, %7, %8, %9, %10, %11, %12, %13, %14, %15, %16, %17, %18, %19, %20, %21, %22, %23, %24, %25, %26, %27, %28, %29, %30, %31, %32, %33, %34, %35, %36, %37, %38, %39, %40, %41, %42, %43, %44, %45, %46, %47}, da, db, p, 1, 1, %51, %52;}"
   : "+f"(d[OFF+0]), "+f"(d[OFF+1]), "+f"(d[OFF+2]), "+f"(d[OFF+3]), "+f"(d[OFF+4]), "+f"(d[OFF+5]), "+f"(d[OFF+6]), "+f"(d[OFF+7]), "+f"(d[OFF+8]), "+f"(d[OFF+9]), "+f"(d[OFF+10]), "+f"(d[OFF+11]), "+f"(d[OFF+12]), "+f"(d[OFF+13]), "+f"(d[OFF+14]), "+f"(d[OFF+15]), "+f"(d[OFF+16]), "+f"(d[OFF+17]), "+f"(d[OFF+18]), "+f"(d[OFF+19]), "+f"(d[OFF+20]), "+f"(d[OFF+21]), "+f"(d[OFF+22]), "+f"(d[OFF+23]), "+f"(d[OFF+24]), "+f"(d[OFF+25]), "+f"(d[OFF+26]), "+f"(d[OFF+27]), "+f"(d[OFF+28]), "+f"(d[OFF+29]), "+f"(d[OFF+30]), "+f"(d[OFF+31]), "+f"(d[OFF+32]), "+f"(d[OFF+33]), "+f"(d[OFF+34]), "+f"(d[OFF+35]), "+f"(d[OFF+36]), "+f"(d[OFF+37]), "+f"(d[OFF+38]), "+f"(d[OFF+39]), "+f"(d[OFF+40]), "+f"(d[OFF+41]), "+f"(d[OFF+42]), "+f"(d[OFF+43]), "+f"(d[OFF+44]), "+f"(d[OFF+45]), "+f"(d[OFF+46]), "+f"(d[OFF+47])
   : "r"(la), "r"(lb), "n"(SD), "n"(TA), "n"(TB), "n"(AO), "n"(AH), "n"(BO), "n"(BH)); } };
template<> struct WGss<128> { template<int OFF,int TA,int TB,uint32_t AO,uint32_t AH,uint32_t BO,uint32_t BH,int SD,int NA> static __device__ __forceinline__ void mma(float (&d)[NA], uint32_t la, uint32_t lb) {
  asm volatile("{.reg .pred p; .reg .b32 x, y; .reg .b64 da, db; setp.ne.b32 p, %66, 0; add.u32 x, %64, %69; mov.b64 da, {x, %70}; add.u32 y, %65, %71; mov.b64 db, {y, %72};\n"
   "wgmma.mma_async.sync.aligned.m64n128k16.f32.bf16.bf16 {%0, %1, %2, %3, %4, %5, %6, %7, %8, %9, %10, %11, %12, %13, %14, %15, %16, %17, %18, %19, %20, %21, %22, %23, %24, %25, %26, %27, %28, %29, %30, %31, %32, %33, %34, %35, %36, %37, %38, %39, %40, %41, %42, %43, %44, %45, %46, %47, %48, %49, %50, %51, %52, %53, %54, %55, %56, %57, %58, %59, %60, %61, %62, %63}, da, db, p, 1, 1, %67, %68;}"
   : "+f"(d[OFF+0]), "+f"(d[OFF+1]), "+f"(d[OFF+2]), "+f"(d[OFF+3]), "+f"(d[OFF+4]), "+f"(d[OFF+5]), "+f"(d[OFF+6]), "+f"(d[OFF+7]), "+f"(d[OFF+8]), "+f"(d[OFF+9]), "+f"(d[OFF+10]), "+f"(d[OFF+11]), "+f"(d[OFF+12]), "+f"(d[OFF+13]), "+f"(d[OFF+14]), "+f"(d[OFF+15]), "+f"(d[OFF+16]), "+f"(d[OFF+17]), "+f"(d[OFF+18]), "+f"(d[OFF+19]), "+f"(d[OFF+20]), "+f"(d[OFF+21]), "+f"(d[OFF+22]), "+f"(d[OFF+23]), "+f"(d[OFF+24]), "+f"(d[OFF+25]), "+f"(d[OFF+26]), "+f"(d[OFF+27]), "+f"(d[OFF+28]), "+f"(d[OFF+29]), "+f"(d[OFF+30]), "+f"(d[OFF+31]), "+f"(d[OFF+32]), "+f"(d[OFF+33]), "+f"(d[OFF+34]), "+f"(d[OFF+35]), "+f"(d[OFF+36]), "+f"(d[OFF+37]), "+f"(d[OFF+38]), "+f"(d[OFF+39]), "+f"(d[OFF+40]), "+f"(d[OFF+41]), "+f"(d[OFF+42]), "+f"(d[OFF+43]), "+f"(d[OFF+44]), "+f"(d[OFF+45]), "+f"(d[OFF+46]), "+f"(d[OFF+47]), "+f"(d[OFF+48]), "+f"(d[OFF+49]), "+f"(d[OFF+50]), "+f"(d[OFF+51]), "+f"(d[OFF+52]), "+f"(d[OFF+53]), "+f"(d[OFF+54]), "+f"(d[OFF+55]), "+f"(d[OFF+56]), "+f"(d[OFF+57]), "+f"(d[OFF+58]), "+f"(d[OFF+59]), "+f"(d[OFF+60]), "+f"(d[OFF+61]), "+f"(d[OFF+62]), "+f"(d[OFF+63])
   : "r"(la), "r"(lb), "n"(SD), "n"(TA), "n"(TB), "n"(AO), "n"(AH), "n"(BO), "n"(BH)); } };

struct Scratch {
    bf16 hT[D_ * S_];
    uint4 part[4 * 16 * 8 * 1024];
    float cs[F_];
    float2 st2[S_];
    uint32_t st1[S_];
    unsigned epoch[32];
    unsigned epoch1[32];
};
__device__ __align__(1024) Scratch g_scratch;

#define DBG2(i) do {} while (0)
#define DBGH2(i) do {} while (0)
#define DBG(i)
#define DBGH(i)
#define DBGT(i)
#define DBG_FLUSH()

__device__ __forceinline__ uint32_t s2u(const void* p) { return (uint32_t)__cvta_generic_to_shared(p); }
__device__ __forceinline__ void mbar_init(uint32_t b, int c) { asm volatile("mbarrier.init.shared::cta.b64 [%0], %1;" ::"r"(b), "r"(c) : "memory"); }
__device__ __forceinline__ void mbar_expect(uint32_t b, int bytes) { asm volatile("mbarrier.arrive.expect_tx.shared::cta.b64 _, [%0], %1;" ::"r"(b), "r"(bytes) : "memory"); }
__device__ __forceinline__ void mbar_arrive(uint32_t b) { asm volatile("mbarrier.arrive.shared::cta.b64 _, [%0];" ::"r"(b) : "memory"); }
__device__ __forceinline__ void mbar_arrive_cluster(uint32_t rb) { asm volatile("mbarrier.arrive.shared::cluster.b64 _, [%0];" ::"r"(rb) : "memory"); }
__device__ __forceinline__ uint32_t mapa(uint32_t a, uint32_t cta) { uint32_t r; asm("mapa.shared::cluster.u32 %0, %1, %2;" : "=r"(r) : "r"(a), "r"(cta)); return r; }
__device__ __forceinline__ void mbar_wait(uint32_t b, int par) {
    asm volatile(
        "{\n.reg .pred p;\n.reg .u32 c;\nmov.u32 c, 0;\n"
        "L_w%=:\n"
        "mbarrier.try_wait.parity.shared::cta.b64 p, [%0], %1;\n"
        "@p bra L_d%=;\n"
        "add.u32 c, c, 1;\nsetp.lt.u32 p, c, 4000000;\n@p bra L_w%=;\ntrap;\n"
        "L_d%=:\n}" ::"r"(b), "r"(par) : "memory");
}
__device__ __forceinline__ void mbar_spin(uint32_t b, int par, int go) {
    asm volatile(
        "{\n.reg .pred p, q;\nsetp.eq.b32 q, %2, 1;\n"
        "L_w%=:\n"
        "mbarrier.try_wait.parity.shared::cta.b64 p, [%0], %1;\n"
        "@p bra L_d%=;\n"
        "@q bra L_w%=;\ntrap;\n"
        "L_d%=:\n}" ::"r"(b), "r"(par), "r"(go) : "memory");
}
__device__ __forceinline__ void tma2d(uint32_t dst, const CUtensorMap* m, int c0, int c1, uint32_t bar) {
    asm volatile("cp.async.bulk.tensor.2d.shared::cluster.global.mbarrier::complete_tx::bytes [%0], [%1, {%3, %4}], [%2];"
                 ::"r"(dst), "l"(m), "r"(bar), "r"(c0), "r"(c1) : "memory");
}
__device__ __forceinline__ void tma3d(uint32_t dst, const CUtensorMap* m, int c0, int c1, int c2, uint32_t bar) {
    asm volatile("cp.async.bulk.tensor.3d.shared::cluster.global.mbarrier::complete_tx::bytes [%0], [%1, {%3, %4, %5}], [%2];"
                 ::"r"(dst), "l"(m), "r"(bar), "r"(c0), "r"(c1), "r"(c2) : "memory");
}
__device__ __forceinline__ void bulk_g2s(uint32_t dst, const void* src, int bytes, uint32_t bar) {
    asm volatile("cp.async.bulk.shared::cluster.global.mbarrier::complete_tx::bytes [%0], [%1], %2, [%3];"
                 ::"r"(dst), "l"(src), "r"(bytes), "r"(bar) : "memory");
}
__device__ __forceinline__ bool elect_one() { uint32_t p; asm volatile("{.reg .pred q; elect.sync _|q, 0xffffffff; selp.u32 %0, 1, 0, q;}" : "=r"(p)); return p; }
__device__ __forceinline__ void wg_fence() { asm volatile("wgmma.fence.sync.aligned;" ::: "memory"); }
__device__ __forceinline__ void wg_commit() { asm volatile("wgmma.commit_group.sync.aligned;" ::: "memory"); }
template <int N> __device__ __forceinline__ void wg_wait() { asm volatile("wgmma.wait_group.sync.aligned %0;" ::"n"(N) : "memory"); }
#define HD __host__ __device__
HD constexpr uint32_t dlo(uint32_t addr, uint32_t lbo) { return (addr >> 4) | ((lbo >> 4) << 16); }
HD constexpr uint32_t dhi(uint32_t sbo, uint32_t sw) { return (sbo >> 4) | (sw << 30); }
constexpr uint32_t SM0 = 1024;
template <int I> struct IC { static constexpr int v = I; };
template <int A, int B, class Fn> __device__ __forceinline__ void sfor(Fn&& fn) { if constexpr (A < B) { fn(IC<A>{}); sfor<A + 1, B>(fn); } }
template <int NA> __device__ __forceinline__ void reg_fence(float (&a)[NA]) {
#pragma unroll
    for (int i = 0; i < NA; i++) asm volatile("" : "+f"(a[i])::"memory");
}
__device__ __forceinline__ uint32_t pack_bf16(float lo, float hi) { uint32_t r; asm("cvt.rn.bf16x2.f32 %0, %1, %2;" : "=r"(r) : "f"(hi), "f"(lo)); return r; }
__device__ __forceinline__ float bf_lo(uint32_t v) { return __uint_as_float(v << 16); }
__device__ __forceinline__ float bf_hi(uint32_t v) { return __uint_as_float(v & 0xffff0000u); }
__device__ __forceinline__ float tanh_fast(float x) { float r; asm("tanh.approx.f32 %0, %1;" : "=f"(r) : "f"(x)); return r; }
__device__ __forceinline__ float4 lds128f(uint32_t a) { float4 v; asm volatile("ld.shared.v4.f32 {%0,%1,%2,%3}, [%4];" : "=f"(v.x), "=f"(v.y), "=f"(v.z), "=f"(v.w) : "r"(a)); return v; }
__device__ __forceinline__ uint4 lds128u(uint32_t a) { uint4 v; asm volatile("ld.shared.v4.b32 {%0,%1,%2,%3}, [%4];" : "=r"(v.x), "=r"(v.y), "=r"(v.z), "=r"(v.w) : "r"(a)); return v; }
__device__ __forceinline__ float lds32f(uint32_t a) { float v; asm volatile("ld.shared.f32 %0, [%1];" : "=f"(v) : "r"(a)); return v; }
__device__ __forceinline__ void sts128f(uint32_t a, float x, float y, float z, float w) { asm volatile("st.shared.v4.f32 [%0], {%1,%2,%3,%4};" ::"r"(a), "f"(x), "f"(y), "f"(z), "f"(w) : "memory"); }
__device__ __forceinline__ float tagf(float x, uint32_t par) { return __uint_as_float((__float_as_uint(x) & ~1u) | par); }
__device__ __forceinline__ uint32_t tagbad(uint32_t a, uint32_t b, uint32_t par) { uint32_t r; asm("lop3.b32 %0, %1, %2, %3, 0x7e;" : "=r"(r) : "r"(a), "r"(b), "r"(par)); return r; }
template <int OFF> __device__ __forceinline__ uint4 ld_tagged(const uint4* p) {
    uint4 v;
    asm volatile("{.reg .b128 t; ld.relaxed.gpu.global.b128 t, [%4 + %5]; mov.b128 {%0,%1,%2,%3}, t;}" : "=r"(v.x), "=r"(v.y), "=r"(v.z), "=r"(v.w) : "l"(p), "n"(OFF * 16) : "memory");
    return v;
}
__device__ __forceinline__ void st_tagged(uint4* p, uint32_t x, uint32_t y, uint32_t z, uint32_t w, uint32_t par) {
    asm volatile("{.reg .b128 t; mov.b128 t, {%1,%2,%3,%4}; st.relaxed.gpu.global.b128 [%0], t;}" ::"l"(p), "r"((x & ~1u) | par), "r"(y), "r"(z), "r"(w) : "memory");
}
__device__ __forceinline__ void cp16(uint32_t dst, const void* src) { asm volatile("cp.async.cg.shared.global [%0], [%1], 16;" ::"r"(dst), "l"(src) : "memory"); }
__device__ __forceinline__ void fence_async_smem() { asm volatile("fence.proxy.async.shared::cta;" ::: "memory"); }
__device__ __forceinline__ float bf_round(float x) { return bf_lo(pack_bf16(x, 0.f)); }
__device__ __forceinline__ float rcp_fast(float x) { float r; asm("rcp.approx.ftz.f32 %0, %1;" : "=f"(r) : "f"(x)); return r; }
__device__ __forceinline__ float sqrt_fast(float x) { float r; asm("sqrt.approx.ftz.f32 %0, %1;" : "=f"(r) : "f"(x)); return r; }
__device__ __forceinline__ uint32_t lds32u(uint32_t a) { uint32_t v; asm volatile("ld.shared.b32 %0, [%1];" : "=r"(v) : "r"(a)); return v; }
__device__ __forceinline__ void sts128u(uint32_t a, uint32_t x, uint32_t y, uint32_t z, uint32_t w) { asm volatile("st.shared.v4.b32 [%0], {%1,%2,%3,%4};" ::"r"(a), "r"(x), "r"(y), "r"(z), "r"(w) : "memory"); }

namespace ffn {
constexpr int A_OFF = 0, A_WG = 73728;
constexpr int W_OFF = 147456, W_ST = 12288, NST = 6;
constexpr int BX_OFF = 221184, BX_COLS = 384;
constexpr int AX_OFF = 227328;
constexpr int RS_OFF = 229376;
constexpr int ST_OFF = 229888;
constexpr int B2_OFF = 230144;
constexpr int BAR_OFF = 230656;
constexpr int SMEM = 231168;
constexpr int B_FULLW = 0, B_EMPTYW = 6, B_FULLA = 12, B_PFULL = 21, B_PE = 29, B_STAT = 31, B_Z = 32, B_BXF = 33, B_P1D = 41, B_BXE = 42, B_TICK = 43, B_DONE = 45, B_N = 46;

#define CHUNKS 128, 128, 96, 96, 64, 64
#define AUGD 2
#define PRIO 1
#define FLAG_ 1
#define XLAG 2
#define LEAN 1
constexpr int NW0 = 3, NA0 = 3;
HD constexpr int chunkN(int c) { constexpr int a[] = {CHUNKS, 0}; return a[c]; }
HD constexpr int numChunks() { int n = 0; while (chunkN(n)) n++; return n; }
constexpr int NCH = numChunks();
HD constexpr int chunkCol(int c) { int a = 0; for (int i = 0; i < c; i++) a += chunkN(i); return a; }
HD constexpr int chunkKS(int c) { return 6144 / chunkN(c); }
HD constexpr int chunkNS(int c) { return 576 / chunkKS(c); }
HD constexpr int chunkSt0(int c) { int a = 0; for (int i = 0; i < c; i++) a += chunkNS(i); return a; }
static_assert(chunkCol(NCH) == 576 && chunkSt0(NCH) == 54 && NCH <= 8, "chunks");
HD constexpr int bxWrap() { int c = 0; while (chunkCol(c + 1) <= BX_COLS) c++; return c; }
HD constexpr int bxCol(int c) { return c < bxWrap() ? chunkCol(c) : chunkCol(c) - chunkCol(bxWrap()); }
static_assert(bxWrap() >= 3 && 576 - chunkCol(bxWrap()) <= chunkCol(2), "bx");
HD constexpr uint64_t packTab(int what) {
    uint64_t r = 0;
    for (int c = 0; c < NCH; c++) r |= (uint64_t)(what == 0 ? chunkN(c) / 32 : what == 1 ? chunkCol(c) / 32 : bxCol(c) / 32) << (8 * c);
    return r;
}

struct Ctx {
    uint32_t bar;
    uint32_t aD;
    uint32_t xD;
    bool lead;
    int go;
    float k00, k01, k10, k11;
};

template <int COL0, int J0, int J1, int NA>
__device__ __forceinline__ void gelu_range(const Ctx& c, const float (&acc)[NA], uint32_t (&H)[144]) {
#pragma unroll
    for (int j = J0; j < J1; j++) {
        const float k0 = (j & 1) ? c.k01 : c.k00, k1 = (j & 1) ? c.k11 : c.k10;
        const float a = acc[2 * j], b = acc[2 * j + 1];
        const float ya = fmaf(a, tanh_fast(a * fmaf(a * a, k1, k0)), a);
        const float yb = fmaf(b, tanh_fast(b * fmaf(b * b, k1, k0)), b);
        H[COL0 / 4 + j] = pack_bf16(ya, yb);
        asm volatile("" : "+r"(H[COL0 / 4 + j])::"memory");
    }
}
template <int C>
__device__ __forceinline__ void aug_mma(const Ctx& c, float (&acc)[chunkN(C) / 2]) {
    WGss<chunkN(C)>::template mma<0, 0, 0, dlo(SM0 + AX_OFF, 0), dhi(128, 0), dlo(SM0 + BX_OFF + bxCol(C) * 16, 0), dhi(128, 0), 1>(acc, c.xD, 0);
}
#define CWAIT(b, p) mbar_spin(b, p, c.go)
template <int C, int s>
__device__ __forceinline__ void p1_mma(const Ctx& c, float (&acc)[chunkN(C) / 2]) {
    constexpr int N = chunkN(C), KS = chunkKS(C), gs = chunkSt0(C) + s;
    if constexpr (s == chunkNS(C) - 1) CWAIT(c.bar + 8 * (B_BXF + C), 0);
    CWAIT(c.bar + 8 * (B_FULLW + gs % NST), (gs / NST) & 1);
    wg_fence();
    sfor<0, KS / 16>([&](auto kk) {
        constexpr int k = kk.v;
        constexpr uint32_t wb = SM0 + W_OFF + (gs % NST) * W_ST;
        constexpr uint32_t bo = (N == 96) ? dlo(wb + k * 1024, KS * 64) : dlo(wb + k * 2048, KS * 128);
        constexpr uint32_t bh = (N == 96) ? dhi(512, 2) : dhi(1024, 1);
        WGss<N>::template mma<0, 1, 1, dlo(SM0 + A_OFF + (s * KS + k * 16) * 128, 0), dhi(1024, 1), bo, bh, (s | k) != 0>(acc, c.aD, 0);
    });
    if constexpr (s == chunkNS(C) - 1) aug_mma<C>(c, acc);
}
__device__ __forceinline__ void retire(const Ctx& c, int slot) {
    wg_wait<1>();
    if (c.lead) mbar_arrive(c.bar + 8 * (B_EMPTYW + slot));
}

__device__ __forceinline__ void chunk0(const Ctx& c, float (&acc)[chunkN(0) / 2]) {
    constexpr int N = chunkN(0), KS = chunkKS(0);
    static_assert(KS <= 64, "");
    int slot = 0, par = 0, prev = 0;
#pragma unroll 1
    for (int s = 0; s < chunkNS(0); s++) {
        CWAIT(c.bar + 8 * (B_FULLA + ((s * KS + KS - 1) >> 6)), 0);
        CWAIT(c.bar + 8 * (B_FULLW + slot), par);
        if (s == 0) { DBG(16); DBGT(61); }
        wg_fence();
        sfor<0, KS / 16>([&](auto kk) {
            constexpr int k = kk.v;
            constexpr uint32_t wb = SM0 + W_OFF;
            constexpr uint32_t bo = (N == 96) ? dlo(wb + k * 1024, KS * 64) : dlo(wb + k * 2048, KS * 128);
            constexpr uint32_t bh = (N == 96) ? dhi(512, 2) : dhi(1024, 1);
            WGss<N>::template mma<0, 1, 1, dlo(SM0 + A_OFF + k * 2048, 0), dhi(1024, 1), bo, bh, 1>(acc, c.aD + s * (KS * 8), slot * (W_ST >> 4));
        });
        wg_commit();
        wg_wait<1>();
        if (c.lead && s > 0) mbar_arrive(c.bar + 8 * (B_EMPTYW + prev));
        prev = slot;
        if (++slot == NST) { slot = 0; par ^= 1; }
    }
}

template <int C, int s, int S0>
__device__ __forceinline__ void chunk_loop(const Ctx& c, float (&acc)[chunkN(C) / 2], float (&prev)[chunkN(C - 1) / 2], uint32_t (&H)[144]) {
    if constexpr (s < chunkNS(C)) {
        constexpr int NP = chunkN(C - 1) / 4, NS = chunkNS(C) - S0;
        p1_mma<C, s>(c, acc);
        wg_commit();
        if constexpr (s >= S0) gelu_range<chunkCol(C - 1), ((s - S0) * NP) / NS, ((s - S0 + 1) * NP) / NS>(c, prev, H);
        retire(c, (chunkSt0(C) + s + NST - 1) % NST);
        if constexpr (s == S0 - 1) reg_fence(prev);
        if constexpr (C == 2 && s == 0) { if (c.lead) mbar_arrive(c.bar + 8 * B_BXE); }
        chunk_loop<C, s + 1, S0>(c, acc, prev, H);
    }
}

template <int PAR, int s>
__device__ __forceinline__ void p2_stage(const Ctx& c, float (&acc)[32], const uint32_t (&H)[144]) {
    CWAIT(c.bar + 8 * (B_FULLW + s), PAR);
    wg_fence();
    sfor<0, 6>([&](auto kk) {
        constexpr int k = kk.v, h0 = s * 24 + 4 * k;
        WGrs<64>::template mma<0, 1, dlo(SM0 + W_OFF + s * W_ST + k * 2048, 0), dhi(1024, 1), (s | k) != 0>(acc, H[h0], H[h0 + 1], H[h0 + 2], H[h0 + 3], 0);
    });
    wg_commit();
}

template <int C>
__device__ __forceinline__ void phase1_rest(Ctx& c, float (&prev)[chunkN(C - 1) / 2], uint32_t (&H)[144], float (&accA)[32], uint32_t pe0Remote) {
    if constexpr (C < NCH) {
        DBG(9 + C);
        float acc[chunkN(C) / 2];
        chunk_loop<C, 0, 1>(c, acc, prev, H);
        phase1_rest<C + 1>(c, acc, H, accA, pe0Remote);
    } else {
        constexpr int NP = chunkN(C - 1) / 4, COL = chunkCol(C - 1);
        constexpr int NS = COL / 96 - 1;
        DBG(3); DBGT(62);
        sfor<0, 6>([&](auto ss) {
            constexpr int s = ss.v;
            p2_stage<1, s>(c, accA, H);
            if constexpr (s > 0 && s <= NS) gelu_range<COL, ((s - 1) * NP) / NS, (s * NP) / NS>(c, prev, H);
            retire(c, (s + 5) % 6);
            if constexpr (s == 0) {
                reg_fence(prev);
                if (c.lead) mbar_arrive_cluster(pe0Remote);
            }
        });
    }
}

__device__ __forceinline__ uint32_t bufoff(int b, int f) { return (((f >> 1) + 1 + b) & 3) * 16384; }
__device__ __forceinline__ uint32_t hadd2(uint32_t a, uint32_t b) { uint32_t r; asm("add.rn.bf16x2 %0, %1, %2;" : "=r"(r) : "r"(a), "r"(b)); return r; }

struct Maps { CUtensorMap w1[3], w2, h; };

__global__ void __launch_bounds__(384, 1) __cluster_dims__(2, 1, 1)
ffn_kernel(Scratch* __restrict__ sc, const bf16* __restrict__ b1, const bf16* __restrict__ w2, const bf16* __restrict__ b2, bf16* __restrict__ out, const __grid_constant__ Maps mp) {
    extern __shared__ __align__(1024) unsigned char smem_raw[];
    const uint32_t sb = s2u(smem_raw);
    if ((sb & 0xFFFFFF) != SM0) __trap();
    const uint32_t bar = sb + BAR_OFF;
    const int wid = __shfl_sync(0xffffffffu, threadIdx.x >> 5, 0);
    const int lane = threadIdx.x & 31;
    if (blockIdx.x < 4) {
        if (wid >= 8) return;
        const uint32_t par = (__ldcg(sc->epoch1) + 1) & 1;
        const int wg = wid >> 2, g0 = (blockIdx.x * 2 + wg) * 9;
        const uint32_t rb = wg * 110592;
        auto load = [&](int i) {
            const int b = i % 3;
#pragma unroll 1
            for (int s = 0; s < 3; s++) tma3d(sb + rb + b * 36864 + s * W_ST, &mp.w1[0], 0, (i & 1) * 288 + s * 96, g0 + (i >> 1), bar + 8 * (wg * 3 + b));
            mbar_expect(bar + 8 * (wg * 3 + b), 36864);
        };
        if ((wid & 3) < 3 && elect_one()) { mbar_init(bar + 8 * (wg * 3 + (wid & 3)), 1); load(wid & 3); }
        asm volatile("bar.sync %0, 128;" ::"r"(1 + wg) : "memory");
        float acc[32];
        uint32_t one = 0x3f803f80u;
        asm volatile("" : "+r"(one));
#pragma unroll 1
        for (int i = 0; i < 18; i++) {
            mbar_wait(bar + 8 * (wg * 3 + i % 3), (i / 3) & 1);
            const uint32_t lb = (rb + (i % 3) * 36864) >> 4;
#pragma unroll 1
            for (int k = 0; k < 6; k++) {
                wg_fence();
                WGrs<64>::template mma_p<0, 1, dlo(SM0, 0), dhi(1024, 1)>(acc, one, one, one, one, lb + k * 384, (i & 1) | k);
                sfor<1, 3>([&](auto kk) { WGrs<64>::template mma<0, 1, dlo(SM0 + kk.v * 2048, 0), dhi(1024, 1), 1>(acc, one, one, one, one, lb + k * 384); });
            }
            wg_commit();
            wg_wait<0>();
            reg_fence(acc);
            asm volatile("bar.sync %0, 128;" ::"r"(1 + wg) : "memory");
            if ((wid & 3) == 1 && i + 3 < 18 && elect_one()) load(i + 3);
            if ((i & 1) && (threadIdx.x & 127) < 4) {
                float* o = sc->cs + (g0 + (i >> 1)) * 64 + 2 * lane;
#pragma unroll
                for (int j = 0; j < 8; j++) asm volatile("st.relaxed.gpu.global.v2.f32 [%0], {%1, %2};" ::"l"(o + 8 * j), "f"(tagf(acc[4 * j], par)), "f"(tagf(acc[4 * j + 1], par)) : "memory");
            }
        }
        return;
    }
    const int bid = blockIdx.x - 4;
    const int m = bid >> 3, f = bid & 7, r = f & 1;
    DBG(0); DBGT(60);
    auto loadW0 = [&](int s) {
        constexpr int N = chunkN(0);
        tma3d(sb + W_OFF + s * W_ST, &mp.w1[N / 32 - 2], 0, s * chunkKS(0), N == 96 ? f * 18 : f * 9, bar + 8 * (B_FULLW + s));
        mbar_expect(bar + 8 * (B_FULLW + s), W_ST);
    };
    if (elect_one()) {
        if (wid < NW0) {
            mbar_init(bar + 8 * (B_FULLW + wid), 1);
            loadW0(wid);
        } else if (wid < NW0 + NA0) {
            asm volatile("prefetch.tensormap [%0];" ::"l"(&mp.h) : "memory");
            mbar_init(bar + 8 * (B_FULLA + wid - NW0), 1);
        } else {
            if (wid >= 8) asm volatile("prefetch.tensormap [%0];" ::"l"(wid == 11 ? &mp.h : wid == 10 ? &mp.w2 : &mp.w1[wid - 8]) : "memory");
#pragma unroll 1
            for (int k = wid - NA0; k < B_N - NA0; k += 12 - NW0 - NA0) {
                const int i = k < B_FULLA ? k : k + NA0;
                mbar_init(bar + 8 * i, ((i >= B_EMPTYW && i < B_FULLA) || i >= B_P1D) ? 8 : (i == B_PE || i == B_PE + 1) ? 4 : i == B_Z ? 3 : 1);
            }
        }
        asm volatile("fence.mbarrier_init.release.cluster;" ::: "memory");
    }
    __syncwarp();
    asm volatile("barrier.cluster.arrive.relaxed.aligned;" ::: "memory");
    if (wid >= NW0 && wid < NW0 + NA0) {
        asm volatile("griddepcontrol.wait;" ::: "memory");
        if (elect_one()) {
            const int i = wid - NW0;
            tma2d(sb + A_OFF + i * 8192, &mp.h, m * 128, i * 64, bar + 8 * (B_FULLA + i));
            tma2d(sb + A_OFF + A_WG + i * 8192, &mp.h, m * 128 + 64, i * 64, bar + 8 * (B_FULLA + i));
            mbar_expect(bar + 8 * (B_FULLA + i), 16384);
        }
        __syncwarp();
    }
    asm volatile("bar.sync 0;" ::: "memory");

    if (wid >= 8) {
        asm volatile("setmaxnreg.dec.sync.aligned.u32 24;");
        if (wid == 8) {
            asm volatile("griddepcontrol.wait;" ::: "memory");
            if (elect_one()) {
#pragma unroll 1
                for (int i = NA0, s = NW0; i < 9; i++, s++) {
                    tma2d(sb + A_OFF + i * 8192, &mp.h, m * 128, i * 64, bar + 8 * (B_FULLA + i));
                    tma2d(sb + A_OFF + A_WG + i * 8192, &mp.h, m * 128 + 64, i * 64, bar + 8 * (B_FULLA + i));
                    mbar_expect(bar + 8 * (B_FULLA + i), 16384);
                    if (s < NST) loadW0(s);
                }
            }
            __syncwarp();
            int slot = 0, par = 0, k = NST * chunkKS(0);
#pragma unroll 1
            for (int C = 0; C < NCH; C++) {
                const int n32 = (packTab(0) >> (8 * C)) & 255, c32 = (packTab(1) >> (8 * C)) & 255;
                const int ks = n32 == 2 ? 96 : n32 == 3 ? 64 : 48, g = n32 == 3 ? f * 18 + c32 : f * 9 + (c32 >> 1);
#pragma unroll 1
                for (; k < 576; k += ks) {
                    mbar_wait(bar + 8 * (B_EMPTYW + slot), par);
                    if (elect_one()) {
                        tma3d(sb + W_OFF + slot * W_ST, &mp.w1[n32 - 2], 0, k, g, bar + 8 * (B_FULLW + slot));
                        mbar_expect(bar + 8 * (B_FULLW + slot), W_ST);
                    }
                    if (++slot == NST) { slot = 0; par ^= 1; }
                }
                k = 0;
            }
#pragma unroll 1
            for (int p = 0; p < 9; p++) {
                const int blk = p == 0 ? 8 : 2 * (((f >> 1) + ((p + 1) >> 1)) & 3) + ((p & 1) ^ r);
#pragma unroll 1
                for (int s = 0; s < 6; s++) {
                    mbar_wait(bar + 8 * (B_EMPTYW + s), p & 1);
                    if (elect_one()) {
                        tma2d(sb + W_OFF + s * W_ST, &mp.w2, blk * 64, f * 576 + s * 96, bar + 8 * (B_FULLW + s));
                        mbar_expect(bar + 8 * (B_FULLW + s), W_ST);
                    }
                }
            }
            if (LEAN) mbar_wait(bar + 8 * B_DONE, 0);
        } else {
            const int hw = wid - 9;
            const uint32_t bb2 = *(const uint32_t*)(b2 + (hw ? 512 : f * 64) + 2 * lane);
            asm volatile("griddepcontrol.wait;" ::: "memory");
            DBGH(hw == 0 ? 30 : 31);
            if (hw < 2 && elect_one()) {
#pragma unroll 1
                for (int i = 0; i < 4; i++) mbar_expect(bar + 8 * (B_PFULL + hw * 4 + i), 8192);
            }
            __syncwarp();
            const unsigned ep = __ldcg(sc->epoch);
            if (hw < 2) asm volatile("st.shared.v2.f32 [%0], {%1, %2};" ::"r"(sb + B2_OFF + hw * 256 + lane * 8), "f"(bf_lo(bb2)), "f"(bf_hi(bb2)) : "memory");
            {
                const int q = lane & 3, ds = ((lane >> 1) & 6) | (lane >> 4);
                const uint32_t la = sb + A_OFF + (f >> 2) * A_WG + ds * 128 + (((2 * (f & 3) + (q >> 1)) ^ ds) << 4) + (q & 1) * 8;
                float v[8];
#pragma unroll
                for (int i = 0; i < 8; i++) v[i] = 0.f;
#pragma unroll 1
                for (int i = hw; i < 9; i += 3) {
                    mbar_wait(bar + 8 * (B_FULLA + i), 0);
#pragma unroll 2
                    for (int j = 0; j < 8; j++) {
                        uint32_t w0, w1;
                        asm volatile("ld.shared.v2.b32 {%0,%1}, [%2];" : "=r"(w0), "=r"(w1) : "r"(la + i * 8192 + j * 1024));
                        const float a0 = bf_lo(w0), a1 = bf_hi(w0), a2 = bf_lo(w1), a3 = bf_hi(w1);
                        v[0] += a0; v[1] += a1; v[2] += a2; v[3] += a3;
                        v[4] = fmaf(a0, a0, v[4]); v[5] = fmaf(a1, a1, v[5]); v[6] = fmaf(a2, a2, v[6]); v[7] = fmaf(a3, a3, v[7]);
                    }
                }
                const bool b4 = lane & 16, b3 = lane & 8, b2_ = lane & 4;
#pragma unroll
                for (int i = 0; i < 4; i++) v[i] = (b4 ? v[4 + i] : v[i]) + __shfl_xor_sync(0xffffffffu, b4 ? v[i] : v[4 + i], 16);
#pragma unroll
                for (int i = 0; i < 2; i++) v[i] = (b3 ? v[2 + i] : v[i]) + __shfl_xor_sync(0xffffffffu, b3 ? v[i] : v[2 + i], 8);
                v[0] = (b2_ ? v[1] : v[0]) + __shfl_xor_sync(0xffffffffu, b2_ ? v[0] : v[1], 4);
                if (hw < 2) {
                    asm volatile("st.shared.f32 [%0], %1;" ::"r"(sb + ST_OFF + hw * 128 + lane * 4), "f"(v[0]) : "memory");
                    asm volatile("bar.arrive 1, 96;" ::: "memory");
                } else {
                    asm volatile("bar.sync 1, 96;" ::: "memory");
                    const float t = (v[0] + lds32f(sb + ST_OFF + lane * 4) + lds32f(sb + ST_OFF + 128 + lane * 4)) * (1.f / D_);
                    const float sq = __shfl_xor_sync(0xffffffffu, t, 16);
                    if (!b4) {
                        const float sg = sqrt_fast(fmaxf(sq - t * t, 0.f) + 1e-5f);
                        asm volatile("st.relaxed.gpu.global.v2.f32 [%0], {%1, %2};" ::"l"(sc->st2 + m * 128 + f * 16 + 4 * q + ((lane >> 2) & 1) + ((lane >> 2) & 2)), "f"(tagf(t, ep & 1)), "f"(tagf(sg, ep & 1)) : "memory");
                    }
                }
            }
            const uint32_t par = __shfl_sync(0xffffffffu, ep & 1, 0);
            if (hw == 2) {
                float2 st[4];
#pragma unroll 1
                for (int it = 0; it < 4000000; it++) {
                    uint32_t bad = 0;
                    sfor<0, 4>([&](auto ii) {
                        asm volatile("ld.relaxed.gpu.global.v2.f32 {%0, %1}, [%2 + %3];" : "=f"(st[ii.v].x), "=f"(st[ii.v].y) : "l"(sc->st2 + m * 128 + lane), "n"(ii.v * 256) : "memory");
                    });
#pragma unroll
                    for (int i = 0; i < 4; i++) bad |= tagbad(__float_as_uint(st[i].x), __float_as_uint(st[i].y), par);
                    if (!__any_sync(0xffffffffu, bad & 1)) break;
                }
#pragma unroll 1
                for (int i = 0; i < 4; i++) {
                    const float sg = st[0].y, hs = 0.5f * sg, nm = -0.5f * st[0].x;
                    st[0] = st[1]; st[1] = st[2]; st[2] = st[3];
                    const float sh = bf_round(hs), mh = bf_round(nm), ml = bf_round(nm - mh);
                    const uint32_t mm = pack_bf16(mh, ml);
                    sts128u(sb + AX_OFF + (i * 32 + lane) * 16, pack_bf16(sh, hs - sh), mm, mm, pack_bf16(nm - mh - ml, mh));
                    asm volatile("st.shared.f32 [%0], %1;" ::"r"(sb + RS_OFF + (i * 32 + lane) * 4), "f"(0.5f * rcp_fast(sg)) : "memory");
                }
                if (lane == 0) asm volatile("st.shared.b32 [%0], %1;" ::"r"(sb + BAR_OFF + 504), "r"(par) : "memory");
                fence_async_smem();
                __syncwarp();
                if (lane == 0) mbar_arrive(bar + 8 * B_STAT);
            } else if (hw == 1) {
                if (lane < 9)
                    asm volatile("cp.async.bulk.prefetch.L2.global [%0], %1;" ::"l"(w2 + (size_t)(f * 576 + m * 36 + lane * 4) * 576), "r"(4608) : "memory");
            } else {
#pragma unroll 1
                for (int C = 0; C < NCH; C++) {
                    const int n32 = (packTab(0) >> (8 * C)) & 255, col = f * 576 + ((packTab(1) >> (8 * C)) & 255) * 32 + lane;
                    const uint32_t a = sb + BX_OFF + ((packTab(2) >> (8 * C)) & 255) * 512 + lane * 16;
                    float cs[4]; uint32_t bv[4];
                    const float* cp = sc->cs + col;
                    const bf16* bp = b1 + col;
                    sfor<0, 4>([&](auto ii) { bv[ii.v] = 0; if (ii.v < n32) asm volatile("ld.global.nc.u16 %0, [%1 + %2];" : "=r"(bv[ii.v]) : "l"(bp), "n"(ii.v * 64)); });
#pragma unroll 1
                    for (int it = 0; it < 4000000; it++) {
                        sfor<0, 4>([&](auto ii) {
                            cs[ii.v] = __uint_as_float(par);
                            if (ii.v < n32) asm volatile("ld.relaxed.gpu.global.f32 %0, [%1 + %2];" : "=f"(cs[ii.v]) : "l"(cp), "n"(ii.v * 128) : "memory");
                        });
                        const uint32_t bad = tagbad(__float_as_uint(cs[0]), __float_as_uint(cs[1]), par) | tagbad(__float_as_uint(cs[2]), __float_as_uint(cs[3]), par);
                        if (!__any_sync(0xffffffffu, bad & 1)) break;
                    }
                    if (C == bxWrap()) mbar_wait(bar + 8 * B_BXE, 0);
#pragma unroll 1
                    for (int i = 0; i < n32; i++) {
                        const float ch = bf_round(cs[0]), cl = bf_round(cs[0] - ch);
                        sts128u(a + i * 512, bv[0] * 0x10001u, pack_bf16(ch, ch), pack_bf16(cl, cl), pack_bf16(ch, cs[0] - ch - cl));
                        cs[0] = cs[1]; cs[1] = cs[2]; cs[2] = cs[3]; bv[0] = bv[1]; bv[1] = bv[2]; bv[2] = bv[3];
                    }
                    fence_async_smem();
                    __syncwarp();
                    if (lane == 0) mbar_arrive(bar + 8 * (B_BXF + C));
                }
            }
            uint32_t lm = (lane & 7) * 128 + ((((lane >> 3) & 1) ^ (lane & 7)) << 4);
            uint32_t tq = sb + (lane & 3) * 8, tg = sb + (lane >> 2) * 4;
            asm volatile("" : "+r"(lm), "+r"(tq), "+r"(tg));
            mbar_wait(bar + 8 * B_P1D, 0);
            DBGH((hw & 1) * 64 + 26);
            const uint32_t yb = sb + A_OFF + bufoff(2, f) + lane * 16;
#pragma unroll 1
            for (int w = hw; w < 8; w += 3) {
                const uint32_t ha = sb + A_OFF + (w >> 2) * A_WG + f * 8192 + (lm ^ ((w & 3) << 5));
                const uint32_t ya = yb + (w >> 2) * A_WG + (w & 3) * 512;
#pragma unroll 1
                for (int j = 0; j < 8; j++) {
                    uint32_t h0, h1;
                    asm volatile("ldmatrix.sync.aligned.m8n8.x2.trans.shared.b16 {%0,%1}, [%2];" : "=r"(h0), "=r"(h1) : "r"(ha + j * 1024));
                    float b0, b1;
                    asm volatile("ld.shared.v2.f32 {%0,%1}, [%2];" : "=f"(b0), "=f"(b1) : "r"(tq + B2_OFF + j * 32));
                    sts128f(ya + j * 2048, bf_lo(h0) + b0, bf_hi(h0) + b1, bf_lo(h1) + b0, bf_hi(h1) + b1);
                }
            }
            DBGH((hw & 1) * 64 + 27);
            const uint32_t ring = sb + A_OFF + (hw >> 1) * A_WG + bufoff(1, f) + (hw & 1) * 8192 + lane * 16;
#pragma unroll 1
            for (int d = hw; d <= 4; d = hw == 2 ? d + 1 : d < 4 ? 4 : 5) {
                const bool p1 = d == 4;
                const int n = p1 && hw < 2 ? 12 : 8, s4 = p1 ? 384 : 4096, s1 = p1 ? 32 : 1024;
                const uint4* g = sc->part + (size_t)(m * 8) * 1024 + (p1 ? (128 + f) * 1024 + hw * 128 : f * 128 + d * 32) + lane;
                mbar_wait(bar + 8 * (B_TICK + p1), 0);
#pragma unroll 1
                for (int it = 0; it < 1000000; it++) {
#pragma unroll 1
                    for (int i = 0; i < n; i++) cp16(ring + i * 512, g + (i >> 2) * s4 + (i & 3) * s1);
                    asm volatile("cp.async.wait_all;" ::: "memory");
                    uint32_t bad = 0;
#pragma unroll 1
                    for (int i = 0; i < n; i += 2) bad |= tagbad(lds32u(ring + i * 512), lds32u(ring + i * 512 + 512), par);
                    if (!__any_sync(0xffffffffu, bad & 1)) break;
                }
                if (p1) {
#pragma unroll 1
                    for (int i = 0; i < n; i++) {
                        const int w = hw + (i >> 2) * 3;
                        const float r0 = lds32f(tg + RS_OFF + w * 64), r1 = lds32f(tg + RS_OFF + w * 64 + 32);
                        const uint32_t ya = yb + (w >> 2) * A_WG + (w & 3) * 512 + (i & 3) * 4096;
                        const uint4 v = lds128u(ring + i * 512);
                        const float4 y0 = lds128f(ya), y1 = lds128f(ya + 2048);
                        sts128f(ya, fmaf(bf_lo(v.x), r0, y0.x), fmaf(bf_hi(v.x), r0, y0.y), fmaf(bf_lo(v.y), r1, y0.z), fmaf(bf_hi(v.y), r1, y0.w));
                        sts128f(ya + 2048, fmaf(bf_lo(v.z), r0, y1.x), fmaf(bf_hi(v.z), r0, y1.y), fmaf(bf_lo(v.w), r1, y1.z), fmaf(bf_hi(v.w), r1, y1.w));
                    }
                } else {
#pragma unroll 1
                    for (int u = 0; u < 2; u++) {
                        float a0 = 0.f, a1 = 0.f, a2 = 0.f, a3 = 0.f;
#pragma unroll 2
                        for (int i = 0; i < 8; i++) {
                            uint32_t v0, v1;
                            asm volatile("ld.shared.v2.b32 {%0,%1}, [%2];" : "=r"(v0), "=r"(v1) : "r"(ring + i * 512 + u * 8));
                            a0 += bf_lo(v0); a1 += bf_hi(v0); a2 += bf_lo(v1); a3 += bf_hi(v1);
                        }
                        const float r0 = lds32f(tg + RS_OFF + f * 64), r1 = lds32f(tg + RS_OFF + f * 64 + 32);
                        uint32_t h0, h1;
                        asm volatile("ldmatrix.sync.aligned.m8n8.x2.trans.shared.b16 {%0,%1}, [%2];" : "=r"(h0), "=r"(h1)
                                     : "r"(sb + A_OFF + (f >> 2) * A_WG + 8 * 8192 + (2 * d + u) * 1024 + (lm ^ ((f & 3) << 5))));
                        float b0, b1;
                        asm volatile("ld.shared.v2.f32 {%0,%1}, [%2];" : "=f"(b0), "=f"(b1) : "r"(tq + B2_OFF + 256 + (2 * d + u) * 32));
                        bf16* o = out + (size_t)(m * 128 + f * 16 + (lane >> 2)) * D_ + 512 + 16 * d + 8 * u + 2 * (lane & 3);
                        *(uint32_t*)o = pack_bf16(fmaf(a0, r0, bf_lo(h0) + b0), fmaf(a1, r0, bf_hi(h0) + b1));
                        *(uint32_t*)(o + 8 * D_) = pack_bf16(fmaf(a2, r1, bf_lo(h1) + b0), fmaf(a3, r1, bf_hi(h1) + b1));
                    }
                }
                DBGH((hw & 1) * 64 + 28 + p1);
            }
            if (bid == 0 && threadIdx.x == 288) sc->epoch1[0] = __ldcg(sc->epoch);
            __syncwarp();
            if (lane == 0) mbar_arrive(bar + 8 * B_Z);
        }
    } else {
        asm volatile("setmaxnreg.inc.sync.aligned.u32 240;");
        Ctx c;
        const int wg = wid >> 2, warp = wid & 3;
        c.bar = bar; c.lead = lane == 0; c.go = gridDim.y;
        c.aD = wg * (A_WG >> 4); c.xD = wg * 64;
        uint32_t H[144];
        float accA[32], accB[32];
        {
            float acc0[chunkN(0) / 2], acc1[chunkN(1) / 2];
#pragma unroll
            for (int i = 0; i < chunkN(0) / 2; i++) acc0[i] = 0.f;
            DBG(1);
            chunk0(c, acc0);
            asm volatile("barrier.cluster.wait.aligned;" ::: "memory");
            DBG(2);
            sfor<0, AUGD + 1>([&](auto ss) {
                constexpr int s = ss.v;
                if constexpr (s == AUGD) { CWAIT(bar + 8 * B_BXF, 0); CWAIT(bar + 8 * B_STAT, 0); DBG(17); }
                p1_mma<1, s>(c, acc1);
                if constexpr (s == AUGD) aug_mma<0>(c, acc0);
                wg_commit();
                retire(c, (chunkSt0(1) + s + NST - 1) % NST);
            });
            const float r0 = lds32f(sb + RS_OFF + (wid * 16 + (lane >> 2)) * 4), r1 = lds32f(sb + RS_OFF + (wid * 16 + 8 + (lane >> 2)) * 4);
            c.k00 = (2.0f * 0.7978845608028654f) * r0; c.k01 = (2.0f * 0.7978845608028654f) * r1;
            c.k10 = (4.0f * 0.044715f) * c.k00 * r0 * r0; c.k11 = (4.0f * 0.044715f) * c.k01 * r1 * r1;
            chunk_loop<1, AUGD + 1, AUGD + 2>(c, acc1, acc0, H);
            phase1_rest<2>(c, acc1, H, accA, mapa(bar + 8 * (B_PE + wg), r ^ 1));
        }
        DBG(4);
        const uint32_t par = __shfl_sync(0xffffffffu, __float_as_uint(lds32f(sb + BAR_OFF + 504)), 0);
        uint32_t sl = sb + A_OFF + wg * A_WG + warp * 512 + lane * 16;
        uint4* gp = sc->part + (size_t)(m * 8) * 1024 + wid * 128 + lane;
        asm volatile("" : "+r"(sl), "+l"(gp));
        if (c.lead) mbar_arrive(bar + 8 * B_P1D);
        const uint4* p2 = gp + (2 * 128 + f) * 1024;
        auto load23 = [&]() {
            sfor<0, 8>([&](auto dd) {
                constexpr int d = dd.v;
                const uint4 v = ld_tagged<(d >> 2) * 128 * 1024 + (d & 3) * 32>(p2);
                accB[4 * d] = __uint_as_float(v.x); accB[4 * d + 1] = __uint_as_float(v.y); accB[4 * d + 2] = __uint_as_float(v.z); accB[4 * d + 3] = __uint_as_float(v.w);
            });
        };
#pragma unroll 1
        for (int I = 1; I <= 4; I++) {
            const uint32_t la = sl + bufoff(0, f) + (I & 1) * 8192;
            uint4* o = gp + ((I - 1) * 128 + ((f + 2 * I - 2) & 7)) * 1024;
            uint4 v = make_uint4(0, 0, 0, 0);
            p2_stage<0, 0>(c, accB, H);
            retire(c, 5);
            reg_fence(accA);
            CWAIT(bar + 8 * (I > 1 ? B_PFULL + wg * 4 + I - 2 : B_PE + wg), 0);
            if (I > 1) v = lds128u(la);
            sfor<0, 4>([&](auto dd) {
                constexpr int d = dd.v, k = 8 * d;
                p2_stage<0, 1 + d>(c, accB, H);
                retire(c, d);
                const uint32_t x = hadd2(pack_bf16(accA[k], accA[k + 1]), v.x), y = hadd2(pack_bf16(accA[k + 2], accA[k + 3]), v.y);
                const uint32_t z = hadd2(pack_bf16(accA[k + 4], accA[k + 5]), v.z), w = hadd2(pack_bf16(accA[k + 6], accA[k + 7]), v.w);
                if (d < 3 && I > 1) v = lds128u(la + (d + 1) * 2048);
                st_tagged(o + d * 32, x, y, z, w, par);
            });
            p2_stage<0, 5>(c, accB, H);
            retire(c, 4);
            DBG(20);
            const uint32_t dst = mapa(sl + bufoff(0, f) + ((I - 1) & 1) * 8192, r ^ 1);
            const uint32_t pf = mapa(bar + 8 * (B_PFULL + wg * 4 + I - 1), r ^ 1);
            sfor<0, 6>([&](auto dd) {
                constexpr int d = dd.v, k = 8 * (d & 3);
                p2_stage<1, d>(c, accA, H);
                retire(c, (d + 5) % 6);
                if constexpr (d == 0) { reg_fence(accB); if (c.lead && I < 3) mbar_arrive(bar + 8 * (B_TICK + I - 1)); }
                if constexpr (d < 4)
                    asm volatile("st.async.weak.shared::cluster.mbarrier::complete_tx::bytes.v4.b32 [%0], {%1,%2,%3,%4}, [%5];" ::"r"(dst + d * 2048),
                                 "r"(pack_bf16(accB[k], accB[k + 1])), "r"(pack_bf16(accB[k + 2], accB[k + 3])), "r"(pack_bf16(accB[k + 4], accB[k + 5])),
                                 "r"(pack_bf16(accB[k + 6], accB[k + 7])), "r"(pf) : "memory");
                if constexpr (d == 3) { if (I == 4) load23(); }
            });
            DBG(4 + I);
        }
        DBG(22);
        const uint32_t yb = sl + bufoff(2, f);
        const float r0 = lds32f(sb + RS_OFF + (wid * 16 + (lane >> 2)) * 4), r1 = lds32f(sb + RS_OFF + (wid * 16 + 8 + (lane >> 2)) * 4);
        CWAIT(bar + 8 * B_Z, 0);
        CWAIT(bar + 8 * (B_PFULL + wg * 4 + 3), 0);
        if (LEAN && c.lead) mbar_arrive(bar + 8 * B_DONE);
        float4 y[8];
        uint4 pe[4];
#pragma unroll
        for (int d = 0; d < 4; d++) pe[d] = lds128u(sl + bufoff(0, f) + 8192 + d * 2048);
#pragma unroll
        for (int j = 0; j < 8; j++) y[j] = lds128f(yb + j * 2048);
#pragma unroll 1
        for (int it = 0; it < 1000000; it++) {
            uint32_t bad = 0;
#pragma unroll
            for (int d = 0; d < 8; d += 2) bad |= tagbad(__float_as_uint(accB[4 * d]), __float_as_uint(accB[4 * d + 4]), par);
            if (!__any_sync(0xffffffffu, bad & 1)) break;
            load23();
        }
        DBG(25);
        wg_wait<0>();
        reg_fence(accA);
        DBG(9);
        const int rq = (lane & 7) + ((lane >> 3) & 1) * 8;
        const uint32_t sa = yb - lane * 16 + (rq >> 2) * 2048 + (rq & 3) * 128 + (((lane >> 4) ^ (lane & 7)) << 4);
        const uint32_t lda = yb - lane * 16 + (lane >> 3) * 128 + (((lane & 7) ^ (lane >> 3)) << 4);
        bf16* op = out + (size_t)(m * 128 + wid * 16 + (lane >> 3)) * D_ + f * 64 + (lane & 7) * 8;
#pragma unroll
        for (int d = 0; d < 4; d++) {
            const uint32_t pw[4] = {pe[d].x, pe[d].y, pe[d].z, pe[d].w};
            const float yy[8] = {y[2 * d].x, y[2 * d].y, y[2 * d].z, y[2 * d].w, y[2 * d + 1].x, y[2 * d + 1].y, y[2 * d + 1].z, y[2 * d + 1].w};
            uint32_t q[4];
#pragma unroll
            for (int i = 0; i < 4; i++) {
                const uint32_t x = hadd2(hadd2(__float_as_uint(accB[4 * d + i]), pw[i]), __float_as_uint(accB[16 + 4 * d + i]));
                const float rs = (i & 1) ? r1 : r0;
                q[i] = pack_bf16(fmaf(accA[8 * d + 2 * i] + bf_lo(x), rs, yy[2 * i]), fmaf(accA[8 * d + 2 * i + 1] + bf_hi(x), rs, yy[2 * i + 1]));
            }
            asm volatile("stmatrix.sync.aligned.m8n8.x4.shared.b16 [%0], {%1,%2,%3,%4};" ::"r"(sa ^ (d << 5)), "r"(q[0]), "r"(q[1]), "r"(q[2]), "r"(q[3]) : "memory");
        }
        __syncwarp();
#pragma unroll
        for (int i = 0; i < 4; i++) *(uint4*)(op + i * 4 * D_) = lds128u((lda ^ ((i & 1) << 6)) + i * 2048);
        DBG(10); DBGT(63);
    }
}
}

namespace cv {
constexpr int KV_UNIT = 12800, V_REL = 7040;
constexpr int KV_OFF = 0;
constexpr int XS_OFF = 51200;
constexpr int W_OFF = 71680, W_PITCH = 8448;
constexpr int K_OFF = 113920, K_PITCH = 4368;
constexpr int XT_OFF = 135808;
constexpr int Z_OFF = 156288, Z_ARR = 4224, Z_SET = 4 * Z_ARR;
constexpr int XR_OFF = 190080;
constexpr int CF_OFF = 208512;
constexpr int BAR_OFF = 208960;
constexpr int SMEM = 209408;
static_assert(3 * Z_SET <= XS_OFF, "");
constexpr int B_LD = 0, B_KF = 4, B_LX = 7, B_UF = 8, B_UF2 = 12, B_XF = 14, B_LR = 15, B_KR = 16, B_ZF = 19, B_N = 29;

__device__ __forceinline__ uint32_t hmul2(uint32_t a, uint32_t b) { uint32_t r; asm("mul.rn.bf16x2 %0, %1, %2;" : "=r"(r) : "r"(a), "r"(b)); return r; }
__device__ __forceinline__ uint32_t hadd2(uint32_t a, uint32_t b) { uint32_t r; asm("add.rn.bf16x2 %0, %1, %2;" : "=r"(r) : "r"(a), "r"(b)); return r; }
__device__ __forceinline__ uint32_t hsub2(uint32_t a, uint32_t b) { uint32_t r; asm("sub.rn.bf16x2 %0, %1, %2;" : "=r"(r) : "r"(a), "r"(b)); return r; }
__device__ __forceinline__ uint32_t hfma2(uint32_t a, uint32_t b, uint32_t c) { uint32_t r; asm("fma.rn.bf16x2 %0, %1, %2, %3;" : "=r"(r) : "r"(a), "r"(b), "r"(c)); return r; }
__device__ __forceinline__ void ldsm4t(uint32_t* r, uint32_t a) {
    asm volatile("ldmatrix.sync.aligned.m8n8.x4.trans.shared.b16 {%0,%1,%2,%3}, [%4];" : "=r"(r[0]), "=r"(r[1]), "=r"(r[2]), "=r"(r[3]) : "r"(a));
}
__device__ __forceinline__ void stas4(uint32_t a, uint32_t x, uint32_t y, uint32_t z, uint32_t w, uint32_t mb) {
    asm volatile("st.async.weak.shared::cluster.mbarrier::complete_tx::bytes.v4.b32 [%0], {%1,%2,%3,%4}, [%5];" ::"r"(a), "r"(x), "r"(y), "r"(z), "r"(w), "r"(mb) : "memory");
}
__device__ __forceinline__ int wpos(int x) { const int j = (x >> 2) & 3, t = (x >> 4) & 3; return ((x & ~63) + 16 * j + 4 * (t ^ (j & 2)) + (x & 3)) * 4; }
__device__ __forceinline__ uint32_t zbase(uint32_t sb, int slot) { return sb + (slot < 2 ? Z_OFF + slot * Z_SET : KV_OFF + (slot - 2) * Z_SET); }

template <int P>
__device__ __forceinline__ void load_a(uint32_t (&a)[8], uint32_t w0, uint32_t w8) {
#pragma unroll
    for (int i = 0; i < 2; i++) {
        a[4 * i] = lds32u(w8 + (2 * P + i) * 512); a[4 * i + 1] = lds32u(w8 + (2 * P + i) * 512 + 256);
        a[4 * i + 2] = lds32u(w0 + (2 * P + i) * 512); a[4 * i + 3] = lds32u(w0 + (2 * P + i) * 512 + 256);
    }
}
template <int P>
__device__ __forceinline__ void retire_cols(float (&acc)[16], float& c0, float& c1, uint32_t za) {
    uint32_t q[4];
    reg_fence(acc);
#pragma unroll
    for (int i = 0; i < 4; i++) {
        q[i] = pack_bf16(acc[4 * i] + c0, acc[4 * i + 1] + c1);
        c0 = acc[4 * i + 2]; c1 = acc[4 * i + 3];
    }
    asm volatile("stmatrix.sync.aligned.m8n8.x4.trans.shared.b16 [%0], {%1,%2,%3,%4};" ::"r"(za + P * 512), "r"(q[0]), "r"(q[1]), "r"(q[2]), "r"(q[3]) : "memory");
}
template <int P, int C0, int N, int SD>
__device__ __forceinline__ void pair_mma(float (&acc)[N / 2], const uint32_t (&a)[8], uint32_t kd) {
    WGrs<N>::template mma<0, 0, dlo(SM0 + K_OFF + 256 + 16 * (C0 - 32 * P), 16), dhi(128, 0), SD>(acc, a[0], a[1], a[2], a[3], kd);
    WGrs<N>::template mma<0, 0, dlo(SM0 + K_OFF + 16 * (C0 - 32 * P), 16), dhi(128, 0), 1>(acc, a[4], a[5], a[6], a[7], kd);
}
__device__ __forceinline__ void conv_slot(uint32_t sb, int slot, int warp, int lane, int go) {
    const uint32_t bar = sb + BAR_OFF;
    const int o = 16 * warp + (lane >> 2) - 2 * (lane & 3);
    const uint32_t wb = sb + W_OFF + slot * W_PITCH + 256;
    const uint32_t w0 = wb + wpos(o), w8 = wb + wpos(o + 8);
    const uint32_t za = zbase(sb, slot) + warp * (Z_ARR + 32) + lane * 16;
    const uint32_t kd = slot * (K_PITCH >> 4);
    const uint32_t ub = bar + 8 * (slot < 2 ? B_UF : B_UF2 + (slot >> 2)), us = slot < 2 ? 8 : 0;
    float blk[8][16], accL[64], c0 = 0.f, c1 = 0.f;
    uint32_t a[3][8];
    mbar_spin(bar + 8 * (B_KR + (slot >> 1)), 0, go);
    if (lane < 2 * warp) sts128u(za - warp * 32, 0, 0, 0, 0);
    mbar_spin(ub, 0, go);
    if (slot < 2) DBG(2);
    load_a<0>(a[0], w0, w8);
    load_a<1>(a[1], w0, w8);
    sfor<0, 8>([&](auto pp) {
        constexpr int p = pp.v;
        if constexpr (p == 4) {
            wg_wait<0>();
#pragma unroll
            for (int i = 0; i < 64; i++) asm volatile("mov.b32 %0, %1;" : "=f"(blk[4 + i / 16][i % 16]) : "f"(accL[i]) : "memory");
        }
        wg_fence();
        sfor<p, (p < 4 ? 4 : 8)>([&](auto bb) { pair_mma<p, 32 * bb.v, 32, p != 0>(blk[bb.v], a[p % 3], kd); });
        if constexpr (p < 4) pair_mma<p, 128, 128, p != 0>(accL, a[p % 3], kd);
        wg_commit();
        if constexpr (p > 0 && p != 4) wg_wait<1>();
        if constexpr ((p & 1) && p < 7) {
            mbar_spin(ub + us * ((p + 1) / 2), 0, go);
            load_a<p + 1>(a[(p + 1) % 3], w0, w8);
            load_a<p + 2>(a[(p + 2) % 3], w0, w8);
        }
        if constexpr (p > 0) retire_cols<p - 1>(blk[p - 1], c0, c1, za);
        if constexpr (p == 4) { __syncwarp(); if (lane == 0) mbar_arrive(bar + 8 * (B_ZF + slot * 2)); }
    });
    wg_wait<0>();
    retire_cols<7>(blk[7], c0, c1, za);
    __syncwarp();
    if (lane == 0) mbar_arrive(bar + 8 * (B_ZF + slot * 2 + 1));
    DBG(slot < 2 ? 4 : slot < 4 ? 7 : 22);
}

struct Maps { CUtensorMap x; };

__global__ void __launch_bounds__(512, 1) __cluster_dims__(8, 1, 1)
conv_kernel(const bf16* __restrict__ kin, const bf16* __restrict__ vin, const bf16* __restrict__ filt, const bf16* __restrict__ sk,
            const bf16* __restrict__ Dv, Scratch* __restrict__ sc, const bf16* __restrict__ x, const bf16* __restrict__ w1, const __grid_constant__ Maps mp) {
    extern __shared__ __align__(1024) unsigned char smem_raw[];
    const uint32_t sb = s2u(smem_raw);
    const uint32_t bar = sb + BAR_OFF;
    const int cl = blockIdx.x >> 3, rank = blockIdx.x & 7, c0 = cl * 40;
    const int ns = cl == 14 ? 2 : 5;
    DBG(0); DBGT(30);
    const int wid = __shfl_sync(0xffffffffu, threadIdx.x >> 5, 0);
    const int lane = threadIdx.x & 31, wg = wid >> 2, warp = wid & 3;
    if ((sb & 0xFFFFFF) != SM0) __trap();
    if (wg < 2) {
        const int id = threadIdx.x, q5 = id / 5, cg = id - q5 * 5, row = rank * 64 + (q5 & 3) * 16 + (q5 >> 2);
        const int off = row * D_ + c0 + (cg < ns ? cg * 8 : 0);
        const bf16 *kp = kin + off, *vp = vin + off;
        uint32_t d = sb + KV_OFF + id * 16;
        if (wid == 7 && lane < 26 && (lane < 4 * ns || lane >= 20) && (lane < 20 + ns || lane == 25))
            cp16(sb + CF_OFF + lane * 16, lane < 20 ? (const void*)(sk + (c0 + 2 * lane) * 4) : lane < 25 ? (const void*)(Dv + c0 + 8 * (lane - 20)) : (const void*)sc->epoch1);
#pragma unroll 1
        for (int c = 0; c < 4; c++, kp += 512 * D_, vp += 512 * D_, d += KV_UNIT) {
            const bool kz = c == 0 && row < 6, vz = c == 0 && row < 2;
            if (id < 240) {
                asm volatile("cp.async.cg.shared.global [%0], [%1], 16, %2;" ::"r"(d), "l"(kz ? kp : kp - 6 * D_), "r"(kz ? 0 : 16) : "memory");
                asm volatile("cp.async.cg.shared.global [%0], [%1], 16, %2;" ::"r"(d + V_REL), "l"(vz ? vp : vp - 2 * D_), "r"(vz ? 0 : 16) : "memory");
            }
            if (id < 200) cp16(d + 3840, kp + 6 * D_);
            if (id < 120) cp16(d + V_REL + 3840, vp + 10 * D_);
            if (c == 0) {
                DBG(14);
                asm volatile("barrier.cluster.arrive.relaxed.aligned;\nbarrier.cluster.wait.aligned;" ::: "memory");
                DBG(1);
            }
            asm volatile("cp.async.mbarrier.arrive.noinc.shared::cta.b64 [%0];" ::"r"(bar + 8 * (B_LD + c)) : "memory");
        }
        asm volatile("setmaxnreg.inc.sync.aligned.u32 184;");
#pragma unroll 1
        for (int slot = wg; slot < ns; slot += 2) conv_slot(sb, slot, warp, lane, gridDim.y);
        DBG(9);
    } else {
        asm volatile("setmaxnreg.dec.sync.aligned.u32 72;");
        const int pw = wid - 8;
        auto load_filter = [&](int j) { bulk_g2s(sb + K_OFF + j * K_PITCH + 272, filt + (size_t)(c0 + 8 * j + rank) * S_, 4096, bar + 8 * (B_KF + (j >> 1))); };
        if (elect_one()) {
#pragma unroll 1
            for (int i = pw; i < B_N; i += 8) {
                mbar_init(bar + 8 * i, i < B_KF ? 256 : i >= B_ZF ? 4 : i == B_KR + 1 ? 6 : i == B_LR ? 2 : 1);
                if (i == B_KF) { load_filter(0); load_filter(1); }
                if (i >= B_KF && i <= B_XF) mbar_expect(bar + 8 * i, (i == B_XF ? ns : (int)((0x2411115122ull >> (4 * (i - B_KF))) & 15)) * 4096);
            }
            asm volatile("fence.mbarrier_init.release.cluster;" ::: "memory");
        }
        __syncwarp();
        DBG(14);
        asm volatile("barrier.cluster.arrive.relaxed.aligned;\nbarrier.cluster.wait.aligned;" ::: "memory");
        DBG(1);
        const uint32_t xr2 = sb + W_OFF + 2 * W_PITCH;
        const int row0 = ns == 2 ? 1792 + rank * 32 : blockIdx.x * 16;
        if (pw == 6) {
#pragma unroll 1
            for (int j = 0; j < ns; j++) {
                if (lane < 16) sts128u(sb + W_OFF + j * W_PITCH + lane * 16, 0, 0, 0, 0);
                if (lane < 17) sts128u(sb + K_OFF + j * K_PITCH + lane * 16, 0, 0, 0, 0);
            }
        }
        if (pw == 5 && lane == 0) asm volatile("prefetch.tensormap [%0];" ::"l"(&mp.x) : "memory");
        mbar_wait(bar + 8 * B_LD, 0);
        const unsigned ep = lds32u(sb + CF_OFF + 400) + 1;
        if (pw < ns) {
            uint32_t la = sb + KV_OFF + pw * 16 + (((~lane & 1) << 2) + ((lane >> 1) & 3)) * 80 + (lane >> 3) * 640;
            uint32_t dst = mapa(sb + W_OFF + pw * W_PITCH + 256 + rank * 256 + (lane & 3) * 16, lane >> 2);
            uint32_t mb = mapa(bar + 8 * (pw < 2 ? B_UF : B_UF2 + (pw >> 2)), lane >> 2);
            uint32_t cw0, cw1;
            asm volatile("ld.shared.v2.b32 {%0,%1}, [%2];" : "=r"(cw0), "=r"(cw1) : "r"(sb + CF_OFF + pw * 64 + (lane >> 2) * 8));
            const uint32_t f0 = __byte_perm(cw0, 0, 0x1010), f1 = __byte_perm(cw0, 0, 0x3232), f2 = __byte_perm(cw1, 0, 0x1010), f3 = __byte_perm(cw1, 0, 0x3232);
#pragma unroll 1
            for (int c = 0; c < 4; c++, la += KV_UNIT, dst += 2048, mb += pw < 2 ? 8 : 0) {
                mbar_wait(bar + 8 * (B_LD + c), 0);
                if (lane == 0) DBGH2(32 + (pw >> 1) * 64 + c * 2 + (pw & 1));
                uint32_t kp[12], vp[12];
                ldsm4t(kp, la); ldsm4t(kp + 4, la + 2560); ldsm4t(kp + 8, la + 5120);
                ldsm4t(vp, la + V_REL); ldsm4t(vp + 4, la + V_REL + 2560);
                asm volatile("ldmatrix.sync.aligned.m8n8.x1.trans.shared.b16 {%0}, [%1];" : "=r"(vp[8]) : "r"(la + V_REL + 5120));
                uint32_t u[9];
                uint32_t ksp = __byte_perm(kp[1], kp[0], 0x5432);
#pragma unroll
                for (int i = 0; i < 9; i++) {
                    const uint32_t ks = __byte_perm(kp[i + 2], kp[i + 1], 0x5432);
                    u[i] = hmul2(hfma2(f0, kp[i + 2], hfma2(f1, ks, hfma2(f2, kp[i + 1], hmul2(f3, ksp)))), vp[i]);
                    ksp = ks;
                }
                if (c == 3 && lane == 0) mbar_arrive(bar + 8 * (B_KR + 1));
                if (pw >= 2 && c < PRIO) mbar_wait(bar + 8 * (B_UF + c), 0);
#pragma unroll
                for (int i = 0; i < 4; i++)
                    stas4((i & 2 ? dst ^ 32 : dst) + i * 64, __byte_perm(u[2 * i + 1], u[2 * i], 0x5432), u[2 * i + 1], __byte_perm(u[2 * i + 2], u[2 * i + 1], 0x5432), u[2 * i + 2], mb);
                if (lane == 0) DBGH2(40 + (pw >> 1) * 64 + c * 2 + (pw & 1));
            }
            asm volatile("griddepcontrol.launch_dependents;" ::: "memory");
        } else if (pw == 5) {
            if (elect_one()) {
                if (FLAG_) mbar_wait(bar + 8 * (B_LD + FLAG_), 0);
#pragma unroll 1
                for (int j = 2; j < ns; j++) load_filter(j);
                if (ns > 2) mbar_wait(bar + 8 * (B_LD + XLAG), 0);
                else bulk_g2s(xr2, x + (size_t)(row0 + 16) * D_, 18432, bar + 8 * B_LR);
                bulk_g2s(sb + XR_OFF, x + (size_t)row0 * D_, 18432, bar + 8 * B_LR);
                mbar_expect(bar + 8 * B_LR, ns == 2 ? 36864 : 18432);
#pragma unroll 1
                for (int c = 0; c < 4; c++) tma3d(sb + XS_OFF + c * 5120, &mp.x, c0, c * 32 + rank * 4, 0, bar + 8 * B_LX);
            }
        } else if (pw == 6) {
#pragma unroll 1
            for (int i = 0; 2 * i < ns; i++) {
                mbar_wait(bar + 8 * (B_KF + i), 0);
                if (lane < ns && (lane >> 1) == i) {
                    const uint32_t ka = sb + K_OFF + lane * K_PITCH + 272, k01 = lds32u(ka), dw = lds32u(sb + CF_OFF + 320 + lane * 16 + (rank >> 1) * 4);
                    asm volatile("st.shared.b16 [%0], %1;" ::"r"(ka), "h"((unsigned short)pack_bf16(bf_lo(k01) + ((rank & 1) ? bf_hi(dw) : bf_lo(dw)), 0.f)) : "memory");
                }
                fence_async_smem();
                __syncwarp();
                if (lane == 0) mbar_arrive(bar + 8 * (B_KR + i));
            }
        } else if (pw == 7) {
            if (ns == 2 || lane < 16) {
                asm volatile("st.relaxed.gpu.global.u32 [%0], %1;" ::"l"(sc->st1 + row0 + lane), "r"(~ep << 31) : "memory");
                sc->st2[row0 + lane] = make_float2(__uint_as_float(~ep & 1), __uint_as_float(~ep & 1));
            }
            if (blockIdx.x == 0 && lane == 0) sc->epoch[0] = ep;
            __syncwarp();
            if (lane == 0) mbar_arrive(bar + 8 * B_LR);
        }
        __syncwarp();
        DBG(10);
        mbar_wait(bar + 8 * B_LR, 0);
        DBG(8);
#pragma unroll 1
        for (int i = 0; i < (ns == 2 ? 2 : 1); i++) {
            const int rl = pw * 2 + (lane >> 4);
            const uint32_t a = (i ? xr2 : sb + XR_OFF) + rl * 1152 + (lane & 15) * 8;
            float s0 = 0.f, s1 = 0.f, q0 = 0.f, q1 = 0.f;
#pragma unroll 3
            for (int k = 0; k < 9; k++) {
                uint32_t w0, w1;
                asm volatile("ld.shared.v2.b32 {%0,%1}, [%2];" : "=r"(w0), "=r"(w1) : "r"(a + k * 128));
                const float d0 = bf_lo(w0), d1 = bf_hi(w0), d2 = bf_lo(w1), d3 = bf_hi(w1);
                s0 += d0 + d1; s1 += d2 + d3;
                q0 = fmaf(d0, d0, fmaf(d1, d1, q0)); q1 = fmaf(d2, d2, fmaf(d3, d3, q1));
            }
            s0 += s1; q0 += q1;
#pragma unroll
            for (int d = 1; d < 16; d *= 2) { s0 += __shfl_xor_sync(0xffffffffu, s0, d); q0 += __shfl_xor_sync(0xffffffffu, q0, d); }
            s0 *= 1.f / D_;
            const uint32_t o = (pack_bf16(s0, rcp_fast(sqrt_fast(fmaxf(q0 * (1.f / D_) - s0 * s0, 0.f) + 1e-5f))) & 0x7fffffffu) | (ep << 31);
            if ((lane & 15) == 0) asm volatile("st.relaxed.gpu.global.u32 [%0], %1;" ::"l"(sc->st1 + row0 + i * 16 + rl), "r"(o) : "memory");
        }
        DBG(11);
        {
            uint32_t la = sb + XS_OFF + (pw & 3) * 5120 + (pw >> 2) * 16 + (((lane & 1) << 2) + ((lane >> 1) & 3)) * 80 + (lane >> 3) * 640;
            uint32_t dst = mapa(sb + XT_OFF + (pw >> 2) * 4096 + ((pw & 3) * 8 + rank) * 128 + (lane & 3) * 16, lane >> 2);
            const uint32_t mb = mapa(bar + 8 * B_XF, lane >> 2);
            mbar_wait(bar + 8 * B_LX, 0);
#pragma unroll 1
            for (int j = pw >> 2; j < ns; j += 2, la += 32, dst += 8192) {
                uint32_t xv[8];
                ldsm4t(xv, la); ldsm4t(xv + 4, la + 2560);
                stas4(dst, xv[0], xv[1], xv[2], xv[3], mb);
                stas4(dst + 64, xv[4], xv[5], xv[6], xv[7], mb);
            }
        }
        DBG(12);
        const int b = threadIdx.x - 256;
        uint4 v0, v1;
#pragma unroll 1
        for (int it = 0; it < 1000000; it++) {
            asm volatile("ld.relaxed.gpu.global.v4.b32 {%0,%1,%2,%3}, [%4];" : "=r"(v0.x), "=r"(v0.y), "=r"(v0.z), "=r"(v0.w) : "l"(sc->st1 + b * 8) : "memory");
            asm volatile("ld.relaxed.gpu.global.v4.b32 {%0,%1,%2,%3}, [%4 + 16];" : "=r"(v1.x), "=r"(v1.y), "=r"(v1.z), "=r"(v1.w) : "l"(sc->st1 + b * 8) : "memory");
            const uint32_t e = ep << 31;
            if (!__any_sync(0xffffffffu, (int)(tagbad(v0.x, v0.y, e) | tagbad(v0.z, v0.w, e) | tagbad(v1.x, v1.y, e) | tagbad(v1.z, v1.w, e)) < 0)) break;
        }
        const uint4 mu = make_uint4(__byte_perm(v0.x, v0.y, 0x5410), __byte_perm(v0.z, v0.w, 0x5410), __byte_perm(v1.x, v1.y, 0x5410), __byte_perm(v1.z, v1.w, 0x5410));
        const uint4 rs = make_uint4(__byte_perm(v0.x, v0.y, 0x7632) & 0x7fff7fffu, __byte_perm(v0.z, v0.w, 0x7632) & 0x7fff7fffu,
                                    __byte_perm(v1.x, v1.y, 0x7632) & 0x7fff7fffu, __byte_perm(v1.z, v1.w, 0x7632) & 0x7fff7fffu);
        if (pw < 3 && blockIdx.x < 108 && elect_one())
            asm volatile("cp.async.bulk.prefetch.L2.global [%0], %1;" ::"l"(w1 + (size_t)(blockIdx.x * 3 + pw) * 8192), "r"(16384) : "memory");
        __syncwarp();
        DBG(13);
        mbar_wait(bar + 8 * B_XF, 0);
        DBG(19);
        uint32_t xa = sb + XT_OFF + (b & ~7) * 16 + (b & 1) * 64 + ((b >> 1) & 3) * 16;
        bf16* ho = sc->hT + (size_t)(c0 + rank) * S_ + b * 8;
#pragma unroll 1
        for (int slot = 0; slot < ns; slot++, xa += 4096, ho += 8 * S_) {
            const uint32_t za = zbase(sb, slot) + b * 16;
            const uint4 xv = lds128u(xa);
            mbar_wait(bar + 8 * (B_ZF + slot * 2 + (wg & 1)), 0);
            const uint4 z0 = lds128u(za), z1 = lds128u(za + Z_ARR), z2 = lds128u(za + 2 * Z_ARR), z3 = lds128u(za + 3 * Z_ARR);
            uint4 h;
            h.x = hfma2(hmul2(hsub2(xv.x, mu.x), rs.x), hadd2(hadd2(z0.x, z1.x), hadd2(z2.x, z3.x)), xv.x);
            h.y = hfma2(hmul2(hsub2(xv.y, mu.y), rs.y), hadd2(hadd2(z0.y, z1.y), hadd2(z2.y, z3.y)), xv.y);
            h.z = hfma2(hmul2(hsub2(xv.z, mu.z), rs.z), hadd2(hadd2(z0.z, z1.z), hadd2(z2.z, z3.z)), xv.z);
            h.w = hfma2(hmul2(hsub2(xv.w, mu.w), rs.w), hadd2(hadd2(z0.w, z1.w), hadd2(z2.w, z3.w)), xv.w);
            *(uint4*)ho = h;
        }
        DBG(9); DBGT(31);
    }
}
}

typedef CUresult (*EncFn)(CUtensorMap*, CUtensorMapDataType, cuuint32_t, void*, const cuuint64_t*, const cuuint64_t*, const cuuint32_t*,
                          const cuuint32_t*, CUtensorMapInterleave, CUtensorMapSwizzle, CUtensorMapL2promotion, CUtensorMapFloatOOBfill);
static void enc(EncFn fn, CUtensorMap* m, int rank, const void* base, const cuuint64_t* dims, const cuuint64_t* strides, const cuuint32_t* box, CUtensorMapSwizzle sw) {
    cuuint32_t es[5] = {1, 1, 1, 1, 1};
    fn(m, CU_TENSOR_MAP_DATA_TYPE_BFLOAT16, rank, (void*)base, dims, strides, box, es, CU_TENSOR_MAP_INTERLEAVE_NONE, sw,
       CU_TENSOR_MAP_L2_PROMOTION_L2_128B, CU_TENSOR_MAP_FLOAT_OOB_FILL_NONE);
}

extern "C" void kernel_launch(void* const* d_in, const int* in_sizes, int n_in, void* d_out, int out_size) {
    const bf16 *x = (const bf16*)d_in[0], *k = (const bf16*)d_in[1], *v = (const bf16*)d_in[2], *sk = (const bf16*)d_in[3],
               *K = (const bf16*)d_in[4], *Dv = (const bf16*)d_in[5], *w1 = (const bf16*)d_in[7], *b1 = (const bf16*)d_in[8],
               *w2 = (const bf16*)d_in[9], *b2 = (const bf16*)d_in[10];
    bf16* out = (bf16*)d_out;
    void* fp = nullptr; cudaDriverEntryPointQueryResult q;
    cudaGetDriverEntryPoint("cuTensorMapEncodeTiled", &fp, cudaEnableDefault, &q);
    EncFn fn = (EncFn)fp;
    void* hT; cudaGetSymbolAddress(&hT, g_scratch);
    Scratch* sc = (Scratch*)hT;
    ffn::Maps mp;
    { cuuint64_t d[2] = {S_, D_}, s[1] = {S_ * 2}; cuuint32_t b[2] = {64, 64}; enc(fn, &mp.h, 2, hT, d, s, b, CU_TENSOR_MAP_SWIZZLE_128B); }
    { cuuint64_t d[3] = {32, D_, F_ / 32}, s[2] = {F_ * 2, 64}; cuuint32_t b[3] = {32, 64, 3}; enc(fn, &mp.w1[1], 3, w1, d, s, b, CU_TENSOR_MAP_SWIZZLE_64B); }
    { cuuint64_t d[3] = {64, D_, F_ / 64}, s[2] = {F_ * 2, 128};
      cuuint32_t b2_[3] = {64, 48, 2}; enc(fn, &mp.w1[2], 3, w1, d, s, b2_, CU_TENSOR_MAP_SWIZZLE_128B);
      cuuint32_t b3_[3] = {64, 96, 1}; enc(fn, &mp.w1[0], 3, w1, d, s, b3_, CU_TENSOR_MAP_SWIZZLE_128B); }
    { cuuint64_t d[2] = {D_, F_}, s[1] = {D_ * 2}; cuuint32_t b[2] = {64, 96}; enc(fn, &mp.w2, 2, w2, d, s, b, CU_TENSOR_MAP_SWIZZLE_128B); }
    cv::Maps cm;
    { cuuint64_t d[3] = {D_, S_ / 16, 16}, s[2] = {16 * D_ * 2, D_ * 2};
      cuuint32_t bm[3] = {40, 4, 16};
      enc(fn, &cm.x, 3, x, d, s, bm, CU_TENSOR_MAP_SWIZZLE_NONE); }
    cudaFuncSetAttribute(ffn::ffn_kernel, cudaFuncAttributeMaxDynamicSharedMemorySize, ffn::SMEM);
    cudaFuncSetAttribute(cv::conv_kernel, cudaFuncAttributeMaxDynamicSharedMemorySize, cv::SMEM);
    cudaStream_t st = cudaStreamPerThread;
    cv::conv_kernel<<<120, 512, cv::SMEM, st>>>(k, v, K, sk, Dv, sc, x, w1, cm);
    cudaLaunchConfig_t cf = {};
    cf.gridDim = dim3(132); cf.blockDim = dim3(384); cf.dynamicSmemBytes = ffn::SMEM; cf.stream = st;
    cudaLaunchAttribute at[1];
    at[0].id = cudaLaunchAttributeProgrammaticStreamSerialization; at[0].val.programmaticStreamSerializationAllowed = 1;
    cf.attrs = at; cf.numAttrs = 1;
    cudaLaunchKernelEx(&cf, ffn::ffn_kernel, sc, b1, w2, b2, out, mp);
}
```

```cpp
#include <cuda_runtime.h>
#include <cuda.h>
#include <cuda_bf16.h>
#include <stdint.h>

typedef __nv_bfloat16 bf16;
constexpr int S_ = 2048, D_ = 576, F_ = 4608;

template<int N> struct WGrs;
template<int N> struct WGss;
template<> struct WGrs<32> { template<int OFF,int TB,uint32_t BO,uint32_t BH,int SD,int NA> static __device__ __forceinline__ void mma(float (&d)[NA], uint32_t a0, uint32_t a1, uint32_t a2, uint32_t a3, uint32_t lb) {
  asm volatile("{.reg .pred p; .reg .b32 y; .reg .b64 db; setp.ne.b32 p, %21, 0; add.u32 y, %20, %23; mov.b64 db, {y, %24};\n"
   "wgmma.mma_async.sync.aligned.m64n32k16.f32.bf16.bf16 {%0, %1, %2, %3, %4, %5, %6, %7, %8, %9, %10, %11, %12, %13, %14, %15}, {%16, %17, %18, %19}, db, p, 1, 1, %22;}"
   : "+f"(d[OFF+0]), "+f"(d[OFF+1]), "+f"(d[OFF+2]), "+f"(d[OFF+3]), "+f"(d[OFF+4]), "+f"(d[OFF+5]), "+f"(d[OFF+6]), "+f"(d[OFF+7]), "+f"(d[OFF+8]), "+f"(d[OFF+9]), "+f"(d[OFF+10]), "+f"(d[OFF+11]), "+f"(d[OFF+12]), "+f"(d[OFF+13]), "+f"(d[OFF+14]), "+f"(d[OFF+15])
   : "r"(a0), "r"(a1), "r"(a2), "r"(a3), "r"(lb), "n"(SD), "n"(TB), "n"(BO), "n"(BH)); }
 template<int OFF,int TB,uint32_t BO,uint32_t BH,int NA> static __device__ __forceinline__ void mma_p(float (&d)[NA], uint32_t a0, uint32_t a1, uint32_t a2, uint32_t a3, uint32_t lb, int sd) {
  asm volatile("{.reg .pred p; .reg .b32 y; .reg .b64 db; setp.ne.b32 p, %21, 0; add.u32 y, %20, %23; mov.b64 db, {y, %24};\n"
   "wgmma.mma_async.sync.aligned.m64n32k16.f32.bf16.bf16 {%0, %1, %2, %3, %4, %5, %6, %7, %8, %9, %10, %11, %12, %13, %14, %15}, {%16, %17, %18, %19}, db, p, 1, 1, %22;}"
   : "+f"(d[OFF+0]), "+f"(d[OFF+1]), "+f"(d[OFF+2]), "+f"(d[OFF+3]), "+f"(d[OFF+4]), "+f"(d[OFF+5]), "+f"(d[OFF+6]), "+f"(d[OFF+7]), "+f"(d[OFF+8]), "+f"(d[OFF+9]), "+f"(d[OFF+10]), "+f"(d[OFF+11]), "+f"(d[OFF+12]), "+f"(d[OFF+13]), "+f"(d[OFF+14]), "+f"(d[OFF+15])
   : "r"(a0), "r"(a1), "r"(a2), "r"(a3), "r"(lb), "r"(sd), "n"(TB), "n"(BO), "n"(BH)); } };
template<> struct WGrs<64> { template<int OFF,int TB,uint32_t BO,uint32_t BH,int SD,int NA> static __device__ __forceinline__ void mma(float (&d)[NA], uint32_t a0, uint32_t a1, uint32_t a2, uint32_t a3, uint32_t lb) {
  asm volatile("{.reg .pred p; .reg .b32 y; .reg .b64 db; setp.ne.b32 p, %37, 0; add.u32 y, %36, %39; mov.b64 db, {y, %40};\n"
   "wgmma.mma_async.sync.aligned.m64n64k16.f32.bf16.bf16 {%0, %1, %2, %3, %4, %5, %6, %7, %8, %9, %10, %11, %12, %13, %14, %15, %16, %17, %18, %19, %20, %21, %22, %23, %24, %25, %26, %27, %28, %29, %30, %31}, {%32, %33, %34, %35}, db, p, 1, 1, %38;}"
   : "+f"(d[OFF+0]), "+f"(d[OFF+1]), "+f"(d[OFF+2]), "+f"(d[OFF+3]), "+f"(d[OFF+4]), "+f"(d[OFF+5]), "+f"(d[OFF+6]), "+f"(d[OFF+7]), "+f"(d[OFF+8]), "+f"(d[OFF+9]), "+f"(d[OFF+10]), "+f"(d[OFF+11]), "+f"(d[OFF+12]), "+f"(d[OFF+13]), "+f"(d[OFF+14]), "+f"(d[OFF+15]), "+f"(d[OFF+16]), "+f"(d[OFF+17]), "+f"(d[OFF+18]), "+f"(d[OFF+19]), "+f"(d[OFF+20]), "+f"(d[OFF+21]), "+f"(d[OFF+22]), "+f"(d[OFF+23]), "+f"(d[OFF+24]), "+f"(d[OFF+25]), "+f"(d[OFF+26]), "+f"(d[OFF+27]), "+f"(d[OFF+28]), "+f"(d[OFF+29]), "+f"(d[OFF+30]), "+f"(d[OFF+31])
   : "r"(a0), "r"(a1), "r"(a2), "r"(a3), "r"(lb), "n"(SD), "n"(TB), "n"(BO), "n"(BH)); }
 template<int OFF,int TB,uint32_t BO,uint32_t BH,int NA> static __device__ __forceinline__ void mma_p(float (&d)[NA], uint32_t a0, uint32_t a1, uint32_t a2, uint32_t a3, uint32_t lb, int sd) {
  asm volatile("{.reg .pred p; .reg .b32 y; .reg .b64 db; setp.ne.b32 p, %37, 0; add.u32 y, %36, %39; mov.b64 db, {y, %40};\n"
   "wgmma.mma_async.sync.aligned.m64n64k16.f32.bf16.bf16 {%0, %1, %2, %3, %4, %5, %6, %7, %8, %9, %10, %11, %12, %13, %14, %15, %16, %17, %18, %19, %20, %21, %22, %23, %24, %25, %26, %27, %28, %29, %30, %31}, {%32, %33, %34, %35}, db, p, 1, 1, %38;}"
   : "+f"(d[OFF+0]), "+f"(d[OFF+1]), "+f"(d[OFF+2]), "+f"(d[OFF+3]), "+f"(d[OFF+4]), "+f"(d[OFF+5]), "+f"(d[OFF+6]), "+f"(d[OFF+7]), "+f"(d[OFF+8]), "+f"(d[OFF+9]), "+f"(d[OFF+10]), "+f"(d[OFF+11]), "+f"(d[OFF+12]), "+f"(d[OFF+13]), "+f"(d[OFF+14]), "+f"(d[OFF+15]), "+f"(d[OFF+16]), "+f"(d[OFF+17]), "+f"(d[OFF+18]), "+f"(d[OFF+19]), "+f"(d[OFF+20]), "+f"(d[OFF+21]), "+f"(d[OFF+22]), "+f"(d[OFF+23]), "+f"(d[OFF+24]), "+f"(d[OFF+25]), "+f"(d[OFF+26]), "+f"(d[OFF+27]), "+f"(d[OFF+28]), "+f"(d[OFF+29]), "+f"(d[OFF+30]), "+f"(d[OFF+31])
   : "r"(a0), "r"(a1), "r"(a2), "r"(a3), "r"(lb), "r"(sd), "n"(TB), "n"(BO), "n"(BH)); } };
template<> struct WGrs<128> { template<int OFF,int TB,uint32_t BO,uint32_t BH,int SD,int NA> static __device__ __forceinline__ void mma(float (&d)[NA], uint32_t a0, uint32_t a1, uint32_t a2, uint32_t a3, uint32_t lb) {
  asm volatile("{.reg .pred p; .reg .b32 y; .reg .b64 db; setp.ne.b32 p, %69, 0; add.u32 y, %68, %71; mov.b64 db, {y, %72};\n"
   "wgmma.mma_async.sync.aligned.m64n128k16.f32.bf16.bf16 {%0, %1, %2, %3, %4, %5, %6, %7, %8, %9, %10, %11, %12, %13, %14, %15, %16, %17, %18, %19, %20, %21, %22, %23, %24, %25, %26, %27, %28, %29, %30, %31, %32, %33, %34, %35, %36, %37, %38, %39, %40, %41, %42, %43, %44, %45, %46, %47, %48, %49, %50, %51, %52, %53, %54, %55, %56, %57, %58, %59, %60, %61, %62, %63}, {%64, %65, %66, %67}, db, p, 1, 1, %70;}"
   : "+f"(d[OFF+0]), "+f"(d[OFF+1]), "+f"(d[OFF+2]), "+f"(d[OFF+3]), "+f"(d[OFF+4]), "+f"(d[OFF+5]), "+f"(d[OFF+6]), "+f"(d[OFF+7]), "+f"(d[OFF+8]), "+f"(d[OFF+9]), "+f"(d[OFF+10]), "+f"(d[OFF+11]), "+f"(d[OFF+12]), "+f"(d[OFF+13]), "+f"(d[OFF+14]), "+f"(d[OFF+15]), "+f"(d[OFF+16]), "+f"(d[OFF+17]), "+f"(d[OFF+18]), "+f"(d[OFF+19]), "+f"(d[OFF+20]), "+f"(d[OFF+21]), "+f"(d[OFF+22]), "+f"(d[OFF+23]), "+f"(d[OFF+24]), "+f"(d[OFF+25]), "+f"(d[OFF+26]), "+f"(d[OFF+27]), "+f"(d[OFF+28]), "+f"(d[OFF+29]), "+f"(d[OFF+30]), "+f"(d[OFF+31]), "+f"(d[OFF+32]), "+f"(d[OFF+33]), "+f"(d[OFF+34]), "+f"(d[OFF+35]), "+f"(d[OFF+36]), "+f"(d[OFF+37]), "+f"(d[OFF+38]), "+f"(d[OFF+39]), "+f"(d[OFF+40]), "+f"(d[OFF+41]), "+f"(d[OFF+42]), "+f"(d[OFF+43]), "+f"(d[OFF+44]), "+f"(d[OFF+45]), "+f"(d[OFF+46]), "+f"(d[OFF+47]), "+f"(d[OFF+48]), "+f"(d[OFF+49]), "+f"(d[OFF+50]), "+f"(d[OFF+51]), "+f"(d[OFF+52]), "+f"(d[OFF+53]), "+f"(d[OFF+54]), "+f"(d[OFF+55]), "+f"(d[OFF+56]), "+f"(d[OFF+57]), "+f"(d[OFF+58]), "+f"(d[OFF+59]), "+f"(d[OFF+60]), "+f"(d[OFF+61]), "+f"(d[OFF+62]), "+f"(d[OFF+63])
   : "r"(a0), "r"(a1), "r"(a2), "r"(a3), "r"(lb), "n"(SD), "n"(TB), "n"(BO), "n"(BH)); }
 template<int OFF,int TB,uint32_t BO,uint32_t BH,int NA> static __device__ __forceinline__ void mma_p(float (&d)[NA], uint32_t a0, uint32_t a1, uint32_t a2, uint32_t a3, uint32_t lb, int sd) {
  asm volatile("{.reg .pred p; .reg .b32 y; .reg .b64 db; setp.ne.b32 p, %69, 0; add.u32 y, %68, %71; mov.b64 db, {y, %72};\n"
   "wgmma.mma_async.sync.aligned.m64n128k16.f32.bf16.bf16 {%0, %1, %2, %3, %4, %5, %6, %7, %8, %9, %10, %11, %12, %13, %14, %15, %16, %17, %18, %19, %20, %21, %22, %23, %24, %25, %26, %27, %28, %29, %30, %31, %32, %33, %34, %35, %36, %37, %38, %39, %40, %41, %42, %43, %44, %45, %46, %47, %48, %49, %50, %51, %52, %53, %54, %55, %56, %57, %58, %59, %60, %61, %62, %63}, {%64, %65, %66, %67}, db, p, 1, 1, %70;}"
   : "+f"(d[OFF+0]), "+f"(d[OFF+1]), "+f"(d[OFF+2]), "+f"(d[OFF+3]), "+f"(d[OFF+4]), "+f"(d[OFF+5]), "+f"(d[OFF+6]), "+f"(d[OFF+7]), "+f"(d[OFF+8]), "+f"(d[OFF+9]), "+f"(d[OFF+10]), "+f"(d[OFF+11]), "+f"(d[OFF+12]), "+f"(d[OFF+13]), "+f"(d[OFF+14]), "+f"(d[OFF+15]), "+f"(d[OFF+16]), "+f"(d[OFF+17]), "+f"(d[OFF+18]), "+f"(d[OFF+19]), "+f"(d[OFF+20]), "+f"(d[OFF+21]), "+f"(d[OFF+22]), "+f"(d[OFF+23]), "+f"(d[OFF+24]), "+f"(d[OFF+25]), "+f"(d[OFF+26]), "+f"(d[OFF+27]), "+f"(d[OFF+28]), "+f"(d[OFF+29]), "+f"(d[OFF+30]), "+f"(d[OFF+31]), "+f"(d[OFF+32]), "+f"(d[OFF+33]), "+f"(d[OFF+34]), "+f"(d[OFF+35]), "+f"(d[OFF+36]), "+f"(d[OFF+37]), "+f"(d[OFF+38]), "+f"(d[OFF+39]), "+f"(d[OFF+40]), "+f"(d[OFF+41]), "+f"(d[OFF+42]), "+f"(d[OFF+43]), "+f"(d[OFF+44]), "+f"(d[OFF+45]), "+f"(d[OFF+46]), "+f"(d[OFF+47]), "+f"(d[OFF+48]), "+f"(d[OFF+49]), "+f"(d[OFF+50]), "+f"(d[OFF+51]), "+f"(d[OFF+52]), "+f"(d[OFF+53]), "+f"(d[OFF+54]), "+f"(d[OFF+55]), "+f"(d[OFF+56]), "+f"(d[OFF+57]), "+f"(d[OFF+58]), "+f"(d[OFF+59]), "+f"(d[OFF+60]), "+f"(d[OFF+61]), "+f"(d[OFF+62]), "+f"(d[OFF+63])
   : "r"(a0), "r"(a1), "r"(a2), "r"(a3), "r"(lb), "r"(sd), "n"(TB), "n"(BO), "n"(BH)); } };
template<> struct WGss<8> { template<int OFF,int TA,int TB,uint32_t AO,uint32_t AH,uint32_t BO,uint32_t BH,int SD,int NA> static __device__ __forceinline__ void mma(float (&d)[NA], uint32_t la, uint32_t lb) {
  asm volatile("{.reg .pred p; .reg .b32 x, y; .reg .b64 da, db; setp.ne.b32 p, %6, 0; add.u32 x, %4, %9; mov.b64 da, {x, %10}; add.u32 y, %5, %11; mov.b64 db, {y, %12};\n"
   "wgmma.mma_async.sync.aligned.m64n8k16.f32.bf16.bf16 {%0, %1, %2, %3}, da, db, p, 1, 1, %7, %8;}"
   : "+f"(d[OFF+0]), "+f"(d[OFF+1]), "+f"(d[OFF+2]), "+f"(d[OFF+3])
   : "r"(la), "r"(lb), "n"(SD), "n"(TA), "n"(TB), "n"(AO), "n"(AH), "n"(BO), "n"(BH)); } };
template<> struct WGss<64> { template<int OFF,int TA,int TB,uint32_t AO,uint32_t AH,uint32_t BO,uint32_t BH,int SD,int NA> static __device__ __forceinline__ void mma(float (&d)[NA], uint32_t la, uint32_t lb) {
  asm volatile("{.reg .pred p; .reg .b32 x, y; .reg .b64 da, db; setp.ne.b32 p, %34, 0; add.u32 x, %32, %37; mov.b64 da, {x, %38}; add.u32 y, %33, %39; mov.b64 db, {y, %40};\n"
   "wgmma.mma_async.sync.aligned.m64n64k16.f32.bf16.bf16 {%0, %1, %2, %3, %4, %5, %6, %7, %8, %9, %10, %11, %12, %13, %14, %15, %16, %17, %18, %19, %20, %21, %22, %23, %24, %25, %26, %27, %28, %29, %30, %31}, da, db, p, 1, 1, %35, %36;}"
   : "+f"(d[OFF+0]), "+f"(d[OFF+1]), "+f"(d[OFF+2]), "+f"(d[OFF+3]), "+f"(d[OFF+4]), "+f"(d[OFF+5]), "+f"(d[OFF+6]), "+f"(d[OFF+7]), "+f"(d[OFF+8]), "+f"(d[OFF+9]), "+f"(d[OFF+10]), "+f"(d[OFF+11]), "+f"(d[OFF+12]), "+f"(d[OFF+13]), "+f"(d[OFF+14]), "+f"(d[OFF+15]), "+f"(d[OFF+16]), "+f"(d[OFF+17]), "+f"(d[OFF+18]), "+f"(d[OFF+19]), "+f"(d[OFF+20]), "+f"(d[OFF+21]), "+f"(d[OFF+22]), "+f"(d[OFF+23]), "+f"(d[OFF+24]), "+f"(d[OFF+25]), "+f"(d[OFF+26]), "+f"(d[OFF+27]), "+f"(d[OFF+28]), "+f"(d[OFF+29]), "+f"(d[OFF+30]), "+f"(d[OFF+31])
   : "r"(la), "r"(lb), "n"(SD), "n"(TA), "n"(TB), "n"(AO), "n"(AH), "n"(BO), "n"(BH)); } };
template<> struct WGss<96> { template<int OFF,int TA,int TB,uint32_t AO,uint32_t AH,uint32_t BO,uint32_t BH,int SD,int NA> static __device__ __forceinline__ void mma(float (&d)[NA], uint32_t la, uint32_t lb) {
  asm volatile("{.reg .pred p; .reg .b32 x, y; .reg .b64 da, db; setp.ne.b32 p, %50, 0; add.u32 x, %48, %53; mov.b64 da, {x, %54}; add.u32 y, %49, %55; mov.b64 db, {y, %56};\n"
   "wgmma.mma_async.sync.aligned.m64n96k16.f32.bf16.bf16 {%0, %1, %2, %3, %4, %5, %6, %7, %8, %9, %10, %11, %12, %13, %14, %15, %16, %17, %18, %19, %20, %21, %22, %23, %24, %25, %26, %27, %28, %29, %30, %31, %32, %33, %34, %35, %36, %37, %38, %39, %40, %41, %42, %43, %44, %45, %46, %47}, da, db, p, 1, 1, %51, %52;}"
   : "+f"(d[OFF+0]), "+f"(d[OFF+1]), "+f"(d[OFF+2]), "+f"(d[OFF+3]), "+f"(d[OFF+4]), "+f"(d[OFF+5]), "+f"(d[OFF+6]), "+f"(d[OFF+7]), "+f"(d[OFF+8]), "+f"(d[OFF+9]), "+f"(d[OFF+10]), "+f"(d[OFF+11]), "+f"(d[OFF+12]), "+f"(d[OFF+13]), "+f"(d[OFF+14]), "+f"(d[OFF+15]), "+f"(d[OFF+16]), "+f"(d[OFF+17]), "+f"(d[OFF+18]), "+f"(d[OFF+19]), "+f"(d[OFF+20]), "+f"(d[OFF+21]), "+f"(d[OFF+22]), "+f"(d[OFF+23]), "+f"(d[OFF+24]), "+f"(d[OFF+25]), "+f"(d[OFF+26]), "+f"(d[OFF+27]), "+f"(d[OFF+28]), "+f"(d[OFF+29]), "+f"(d[OFF+30]), "+f"(d[OFF+31]), "+f"(d[OFF+32]), "+f"(d[OFF+33]), "+f"(d[OFF+34]), "+f"(d[OFF+35]), "+f"(d[OFF+36]), "+f"(d[OFF+37]), "+f"(d[OFF+38]), "+f"(d[OFF+39]), "+f"(d[OFF+40]), "+f"(d[OFF+41]), "+f"(d[OFF+42]), "+f"(d[OFF+43]), "+f"(d[OFF+44]), "+f"(d[OFF+45]), "+f"(d[OFF+46]), "+f"(d[OFF+47])
   : "r"(la), "r"(lb), "n"(SD), "n"(TA), "n"(TB), "n"(AO), "n"(AH), "n"(BO), "n"(BH)); } };
template<> struct WGss<128> { template<int OFF,int TA,int TB,uint32_t AO,uint32_t AH,uint32_t BO,uint32_t BH,int SD,int NA> static __device__ __forceinline__ void mma(float (&d)[NA], uint32_t la, uint32_t lb) {
  asm volatile("{.reg .pred p; .reg .b32 x, y; .reg .b64 da, db; setp.ne.b32 p, %66, 0; add.u32 x, %64, %69; mov.b64 da, {x, %70}; add.u32 y, %65, %71; mov.b64 db, {y, %72};\n"
   "wgmma.mma_async.sync.aligned.m64n128k16.f32.bf16.bf16 {%0, %1, %2, %3, %4, %5, %6, %7, %8, %9, %10, %11, %12, %13, %14, %15, %16, %17, %18, %19, %20, %21, %22, %23, %24, %25, %26, %27, %28, %29, %30, %31, %32, %33, %34, %35, %36, %37, %38, %39, %40, %41, %42, %43, %44, %45, %46, %47, %48, %49, %50, %51, %52, %53, %54, %55, %56, %57, %58, %59, %60, %61, %62, %63}, da, db, p, 1, 1, %67, %68;}"
   : "+f"(d[OFF+0]), "+f"(d[OFF+1]), "+f"(d[OFF+2]), "+f"(d[OFF+3]), "+f"(d[OFF+4]), "+f"(d[OFF+5]), "+f"(d[OFF+6]), "+f"(d[OFF+7]), "+f"(d[OFF+8]), "+f"(d[OFF+9]), "+f"(d[OFF+10]), "+f"(d[OFF+11]), "+f"(d[OFF+12]), "+f"(d[OFF+13]), "+f"(d[OFF+14]), "+f"(d[OFF+15]), "+f"(d[OFF+16]), "+f"(d[OFF+17]), "+f"(d[OFF+18]), "+f"(d[OFF+19]), "+f"(d[OFF+20]), "+f"(d[OFF+21]), "+f"(d[OFF+22]), "+f"(d[OFF+23]), "+f"(d[OFF+24]), "+f"(d[OFF+25]), "+f"(d[OFF+26]), "+f"(d[OFF+27]), "+f"(d[OFF+28]), "+f"(d[OFF+29]), "+f"(d[OFF+30]), "+f"(d[OFF+31]), "+f"(d[OFF+32]), "+f"(d[OFF+33]), "+f"(d[OFF+34]), "+f"(d[OFF+35]), "+f"(d[OFF+36]), "+f"(d[OFF+37]), "+f"(d[OFF+38]), "+f"(d[OFF+39]), "+f"(d[OFF+40]), "+f"(d[OFF+41]), "+f"(d[OFF+42]), "+f"(d[OFF+43]), "+f"(d[OFF+44]), "+f"(d[OFF+45]), "+f"(d[OFF+46]), "+f"(d[OFF+47]), "+f"(d[OFF+48]), "+f"(d[OFF+49]), "+f"(d[OFF+50]), "+f"(d[OFF+51]), "+f"(d[OFF+52]), "+f"(d[OFF+53]), "+f"(d[OFF+54]), "+f"(d[OFF+55]), "+f"(d[OFF+56]), "+f"(d[OFF+57]), "+f"(d[OFF+58]), "+f"(d[OFF+59]), "+f"(d[OFF+60]), "+f"(d[OFF+61]), "+f"(d[OFF+62]), "+f"(d[OFF+63])
   : "r"(la), "r"(lb), "n"(SD), "n"(TA), "n"(TB), "n"(AO), "n"(AH), "n"(BO), "n"(BH)); } };

struct Scratch {
    bf16 hT[D_ * S_];
    uint4 part[4 * 16 * 8 * 1024];
    uint4 bx[F_];
    uint4 st2[S_];
    uint32_t st1[S_];
    unsigned epoch[32];
    unsigned epoch1[32];
};
__device__ __align__(1024) Scratch g_scratch;

#define DBG2(i) do {} while (0)
#define DBGH2(i) do {} while (0)
#define DBG(i)
#define DBGH(i)
#define DBGT(i)
#define DBG_FLUSH()

__device__ __forceinline__ uint32_t s2u(const void* p) { return (uint32_t)__cvta_generic_to_shared(p); }
__device__ __forceinline__ void mbar_init(uint32_t b, int c) { asm volatile("mbarrier.init.shared::cta.b64 [%0], %1;" ::"r"(b), "r"(c) : "memory"); }
__device__ __forceinline__ void mbar_expect(uint32_t b, int bytes) { asm volatile("mbarrier.arrive.expect_tx.shared::cta.b64 _, [%0], %1;" ::"r"(b), "r"(bytes) : "memory"); }
__device__ __forceinline__ void mbar_arrive(uint32_t b) { asm volatile("mbarrier.arrive.shared::cta.b64 _, [%0];" ::"r"(b) : "memory"); }
__device__ __forceinline__ void mbar_arrive_cluster(uint32_t rb) { asm volatile("mbarrier.arrive.shared::cluster.b64 _, [%0];" ::"r"(rb) : "memory"); }
__device__ __forceinline__ uint32_t mapa(uint32_t a, uint32_t cta) { uint32_t r; asm("mapa.shared::cluster.u32 %0, %1, %2;" : "=r"(r) : "r"(a), "r"(cta)); return r; }
__device__ __forceinline__ void mbar_wait(uint32_t b, int par) {
    asm volatile(
        "{\n.reg .pred p;\n.reg .u32 c;\nmov.u32 c, 0;\n"
        "L_w%=:\n"
        "mbarrier.try_wait.parity.shared::cta.b64 p, [%0], %1;\n"
        "@p bra L_d%=;\n"
        "add.u32 c, c, 1;\nsetp.lt.u32 p, c, 4000000;\n@p bra L_w%=;\ntrap;\n"
        "L_d%=:\n}" ::"r"(b), "r"(par) : "memory");
}
__device__ __forceinline__ void mbar_doze(uint32_t b) {
    asm volatile(
        "{\n.reg .pred p;\n.reg .u32 c;\nmov.u32 c, 0;\n"
        "L_w%=:\n"
        "mbarrier.try_wait.parity.shared::cta.b64 p, [%0], 0, 2000;\n"
        "@p bra L_d%=;\n"
        "add.u32 c, c, 1;\nsetp.lt.u32 p, c, 1000000;\n@p bra L_w%=;\ntrap;\n"
        "L_d%=:\n}" ::"r"(b) : "memory");
}
__device__ __forceinline__ void mbar_spin(uint32_t b, int par, int go) {
    asm volatile(
        "{\n.reg .pred p, q;\nsetp.eq.b32 q, %2, 1;\n"
        "L_w%=:\n"
        "mbarrier.try_wait.parity.shared::cta.b64 p, [%0], %1;\n"
        "@p bra L_d%=;\n"
        "@q bra L_w%=;\ntrap;\n"
        "L_d%=:\n}" ::"r"(b), "r"(par), "r"(go) : "memory");
}
__device__ __forceinline__ void tma2d(uint32_t dst, const CUtensorMap* m, int c0, int c1, uint32_t bar) {
    asm volatile("cp.async.bulk.tensor.2d.shared::cluster.global.mbarrier::complete_tx::bytes [%0], [%1, {%3, %4}], [%2];"
                 ::"r"(dst), "l"(m), "r"(bar), "r"(c0), "r"(c1) : "memory");
}
__device__ __forceinline__ void tma3d(uint32_t dst, const CUtensorMap* m, int c0, int c1, int c2, uint32_t bar) {
    asm volatile("cp.async.bulk.tensor.3d.shared::cluster.global.mbarrier::complete_tx::bytes [%0], [%1, {%3, %4, %5}], [%2];"
                 ::"r"(dst), "l"(m), "r"(bar), "r"(c0), "r"(c1), "r"(c2) : "memory");
}
__device__ __forceinline__ void bulk_g2s(uint32_t dst, const void* src, int bytes, uint32_t bar) {
    asm volatile("cp.async.bulk.shared::cluster.global.mbarrier::complete_tx::bytes [%0], [%1], %2, [%3];"
                 ::"r"(dst), "l"(src), "r"(bytes), "r"(bar) : "memory");
}
__device__ __forceinline__ bool elect_one() { uint32_t p; asm volatile("{.reg .pred q; elect.sync _|q, 0xffffffff; selp.u32 %0, 1, 0, q;}" : "=r"(p)); return p; }
__device__ __forceinline__ void wg_fence() { asm volatile("wgmma.fence.sync.aligned;" ::: "memory"); }
__device__ __forceinline__ void wg_commit() { asm volatile("wgmma.commit_group.sync.aligned;" ::: "memory"); }
template <int N> __device__ __forceinline__ void wg_wait() { asm volatile("wgmma.wait_group.sync.aligned %0;" ::"n"(N) : "memory"); }
#define HD __host__ __device__
HD constexpr uint32_t dlo(uint32_t addr, uint32_t lbo) { return (addr >> 4) | ((lbo >> 4) << 16); }
HD constexpr uint32_t dhi(uint32_t sbo, uint32_t sw) { return (sbo >> 4) | (sw << 30); }
constexpr uint32_t SM0 = 1024;
template <int I> struct IC { static constexpr int v = I; };
template <int A, int B, class Fn> __device__ __forceinline__ void sfor(Fn&& fn) { if constexpr (A < B) { fn(IC<A>{}); sfor<A + 1, B>(fn); } }
template <int NA> __device__ __forceinline__ void reg_fence(float (&a)[NA]) {
#pragma unroll
    for (int i = 0; i < NA; i++) asm volatile("" : "+f"(a[i])::"memory");
}
__device__ __forceinline__ uint32_t pack_bf16(float lo, float hi) { uint32_t r; asm("cvt.rn.bf16x2.f32 %0, %1, %2;" : "=r"(r) : "f"(hi), "f"(lo)); return r; }
__device__ __forceinline__ float bf_lo(uint32_t v) { return __uint_as_float(v << 16); }
__device__ __forceinline__ float bf_hi(uint32_t v) { return __uint_as_float(v & 0xffff0000u); }
__device__ __forceinline__ float tanh_fast(float x) { float r; asm("tanh.approx.f32 %0, %1;" : "=f"(r) : "f"(x)); return r; }
__device__ __forceinline__ float4 lds128f(uint32_t a) { float4 v; asm volatile("ld.shared.v4.f32 {%0,%1,%2,%3}, [%4];" : "=f"(v.x), "=f"(v.y), "=f"(v.z), "=f"(v.w) : "r"(a)); return v; }
__device__ __forceinline__ uint4 lds128u(uint32_t a) { uint4 v; asm volatile("ld.shared.v4.b32 {%0,%1,%2,%3}, [%4];" : "=r"(v.x), "=r"(v.y), "=r"(v.z), "=r"(v.w) : "r"(a)); return v; }
__device__ __forceinline__ float lds32f(uint32_t a) { float v; asm volatile("ld.shared.f32 %0, [%1];" : "=f"(v) : "r"(a)); return v; }
__device__ __forceinline__ void sts128f(uint32_t a, float x, float y, float z, float w) { asm volatile("st.shared.v4.f32 [%0], {%1,%2,%3,%4};" ::"r"(a), "f"(x), "f"(y), "f"(z), "f"(w) : "memory"); }
__device__ __forceinline__ float tagf(float x, uint32_t par) { return __uint_as_float((__float_as_uint(x) & ~1u) | par); }
__device__ __forceinline__ uint32_t tagbad(uint32_t a, uint32_t b, uint32_t par) { uint32_t r; asm("lop3.b32 %0, %1, %2, %3, 0x7e;" : "=r"(r) : "r"(a), "r"(b), "r"(par)); return r; }
template <int OFF> __device__ __forceinline__ uint4 ld_tagged(const uint4* p) {
    uint4 v;
    asm volatile("{.reg .b128 t; ld.relaxed.gpu.global.b128 t, [%4 + %5]; mov.b128 {%0,%1,%2,%3}, t;}" : "=r"(v.x), "=r"(v.y), "=r"(v.z), "=r"(v.w) : "l"(p), "n"(OFF * 16) : "memory");
    return v;
}
__device__ __forceinline__ void st_tagged(uint4* p, uint32_t x, uint32_t y, uint32_t z, uint32_t w, uint32_t par) {
    asm volatile("{.reg .b128 t; mov.b128 t, {%1,%2,%3,%4}; st.relaxed.gpu.global.b128 [%0], t;}" ::"l"(p), "r"((x & ~1u) | par), "r"(y), "r"(z), "r"(w) : "memory");
}
__device__ __forceinline__ void cp16(uint32_t dst, const void* src) { asm volatile("cp.async.cg.shared.global [%0], [%1], 16;" ::"r"(dst), "l"(src) : "memory"); }
__device__ __forceinline__ void fence_async_smem() { asm volatile("fence.proxy.async.shared::cta;" ::: "memory"); }
__device__ __forceinline__ float bf_round(float x) { return bf_lo(pack_bf16(x, 0.f)); }
__device__ __forceinline__ float rcp_fast(float x) { float r; asm("rcp.approx.ftz.f32 %0, %1;" : "=f"(r) : "f"(x)); return r; }
__device__ __forceinline__ float sqrt_fast(float x) { float r; asm("sqrt.approx.ftz.f32 %0, %1;" : "=f"(r) : "f"(x)); return r; }
__device__ __forceinline__ uint32_t lds32u(uint32_t a) { uint32_t v; asm volatile("ld.shared.b32 %0, [%1];" : "=r"(v) : "r"(a)); return v; }
__device__ __forceinline__ void sts128u(uint32_t a, uint32_t x, uint32_t y, uint32_t z, uint32_t w) { asm volatile("st.shared.v4.b32 [%0], {%1,%2,%3,%4};" ::"r"(a), "r"(x), "r"(y), "r"(z), "r"(w) : "memory"); }

namespace ffn {
constexpr int A_OFF = 0, A_WG = 73728;
constexpr int W_OFF = 147456, W_ST = 12288, NST = 6;
constexpr int BX_OFF = 221184, BX_COLS = 384;
constexpr int AX_OFF = 227328;
constexpr int RS_OFF = 229376;
constexpr int ST_OFF = 229888;
constexpr int B2_OFF = 230144;
constexpr int BAR_OFF = 230656;
constexpr int SMEM = 231168;
constexpr int B_FULLW = 0, B_EMPTYW = 6, B_FULLA = 12, B_PFULL = 21, B_PE = 29, B_STAT = 31, B_Z = 32, B_BXF = 33, B_P1D = 41, B_BXE = 42, B_TICK = 43, B_DONE = 45, B_N = 46;

#define CHUNKS 128, 128, 96, 96, 64, 64
#define AUGD 2
#define PRIO 1
#define FLAG_ 1
#define XLAG 2
#define TRIG 1
#define SPLIT 0
#define PRES 0
#define XSL 0
#define SUNR_ 3
#define EARLY 0
#define CPLAG 0
#define KPF 0
#define KPL 0
#define DOZE 1
#define REMAP 1
#define SKEW 7
#define XFIRST 0
#define PFPOS 1
#define TFIRST 1
#define POLLW 1
#define BACKOFF 100
#define EPI 0
#define LPAT 0x3d55
#define LEAN 1
#define NW0 1
#define NW1 1
constexpr int NA0 = 0;
HD constexpr int chunkN(int c) { constexpr int a[] = {CHUNKS, 0}; return a[c]; }
HD constexpr int numChunks() { int n = 0; while (chunkN(n)) n++; return n; }
constexpr int NCH = numChunks();
HD constexpr int chunkCol(int c) { int a = 0; for (int i = 0; i < c; i++) a += chunkN(i); return a; }
HD constexpr int chunkKS(int c) { return 6144 / chunkN(c); }
HD constexpr int chunkNS(int c) { return 576 / chunkKS(c); }
HD constexpr int chunkSt0(int c) { int a = 0; for (int i = 0; i < c; i++) a += chunkNS(i); return a; }
static_assert(chunkCol(NCH) == 576 && chunkSt0(NCH) == 54 && NCH <= 8, "chunks");
HD constexpr int bxWrap() { int c = 0; while (chunkCol(c + 1) <= BX_COLS) c++; return c; }
HD constexpr int bxCol(int c) { return c < bxWrap() ? chunkCol(c) : chunkCol(c) - chunkCol(bxWrap()); }
static_assert(bxWrap() >= 3 && 576 - chunkCol(bxWrap()) <= chunkCol(2), "bx");
HD constexpr uint64_t packTab(int what) {
    uint64_t r = 0;
    for (int c = 0; c < NCH; c++) r |= (uint64_t)(what == 0 ? chunkN(c) / 32 : what == 1 ? chunkCol(c) / 32 : bxCol(c) / 32) << (8 * c);
    return r;
}

struct Ctx {
    uint32_t bar;
    uint32_t aD;
    uint32_t xD;
    bool lead;
    int go;
    float k00, k01, k10, k11;
};

template <int COL0, int J0, int J1, int NA>
__device__ __forceinline__ void gelu_range(const Ctx& c, const float (&acc)[NA], uint32_t (&H)[144]) {
#pragma unroll
    for (int j = J0; j < J1; j++) {
        const float k0 = (j & 1) ? c.k01 : c.k00, k1 = (j & 1) ? c.k11 : c.k10;
        const float a = acc[2 * j], b = acc[2 * j + 1];
        const float ya = fmaf(a, tanh_fast(a * fmaf(a * a, k1, k0)), a);
        const float yb = fmaf(b, tanh_fast(b * fmaf(b * b, k1, k0)), b);
        H[COL0 / 4 + j] = pack_bf16(ya, yb);
        asm volatile("" : "+r"(H[COL0 / 4 + j])::"memory");
    }
}
template <int C>
__device__ __forceinline__ void aug_mma(const Ctx& c, float (&acc)[chunkN(C) / 2]) {
    WGss<chunkN(C)>::template mma<0, 0, 0, dlo(SM0 + AX_OFF, 0), dhi(128, 0), dlo(SM0 + BX_OFF + bxCol(C) * 16, 0), dhi(128, 0), 1>(acc, c.xD, 0);
}
#define CWAIT(b, p) mbar_spin(b, p, c.go)
template <int C, int s>
__device__ __forceinline__ void p1_mma(const Ctx& c, float (&acc)[chunkN(C) / 2]) {
    constexpr int N = chunkN(C), KS = chunkKS(C), gs = chunkSt0(C) + s;
    if constexpr (s == chunkNS(C) - 1) CWAIT(c.bar + 8 * (B_BXF + C), 0);
    CWAIT(c.bar + 8 * (B_FULLW + gs % NST), (gs / NST) & 1);
    wg_fence();
    sfor<0, KS / 16>([&](auto kk) {
        constexpr int k = kk.v;
        constexpr uint32_t wb = SM0 + W_OFF + (gs % NST) * W_ST;
        constexpr uint32_t bo = (N == 96) ? dlo(wb + k * 1024, KS * 64) : dlo(wb + k * 2048, KS * 128);
        constexpr uint32_t bh = (N == 96) ? dhi(512, 2) : dhi(1024, 1);
        WGss<N>::template mma<0, 1, 1, dlo(SM0 + A_OFF + (s * KS + k * 16) * 128, 0), dhi(1024, 1), bo, bh, (s | k) != 0>(acc, c.aD, 0);
    });
    if constexpr (s == chunkNS(C) - 1) aug_mma<C>(c, acc);
}
__device__ __forceinline__ void retire(const Ctx& c, int slot) {
    wg_wait<1>();
    if (c.lead) mbar_arrive(c.bar + 8 * (B_EMPTYW + slot));
}

__device__ __forceinline__ void chunk0(const Ctx& c, float (&acc)[chunkN(0) / 2]) {
    constexpr int N = chunkN(0), KS = chunkKS(0);
    static_assert(KS <= 64, "");
    int slot = 0, par = 0, prev = 0;
#pragma unroll 1
    for (int s = 0; s < chunkNS(0); s++) {
        CWAIT(c.bar + 8 * (B_FULLA + ((s * KS + KS - 1) >> 6)), 0);
        CWAIT(c.bar + 8 * (B_FULLW + slot), par);
        if (s == 0) { DBG(16); DBGT(61); }
        wg_fence();
        sfor<0, KS / 16>([&](auto kk) {
            constexpr int k = kk.v;
            constexpr uint32_t wb = SM0 + W_OFF;
            constexpr uint32_t bo = (N == 96) ? dlo(wb + k * 1024, KS * 64) : dlo(wb + k * 2048, KS * 128);
            constexpr uint32_t bh = (N == 96) ? dhi(512, 2) : dhi(1024, 1);
            WGss<N>::template mma<0, 1, 1, dlo(SM0 + A_OFF + k * 2048, 0), dhi(1024, 1), bo, bh, 1>(acc, c.aD + s * (KS * 8), slot * (W_ST >> 4));
        });
        wg_commit();
        wg_wait<1>();
        if (c.lead && s > 0) mbar_arrive(c.bar + 8 * (B_EMPTYW + prev));
        prev = slot;
        if (++slot == NST) { slot = 0; par ^= 1; }
    }
}

template <int C, int s, int S0>
__device__ __forceinline__ void chunk_loop(const Ctx& c, float (&acc)[chunkN(C) / 2], float (&prev)[chunkN(C - 1) / 2], uint32_t (&H)[144]) {
    if constexpr (s < chunkNS(C)) {
        constexpr int NP = chunkN(C - 1) / 4, NS = chunkNS(C) - S0;
        p1_mma<C, s>(c, acc);
        wg_commit();
        if constexpr (s >= S0) gelu_range<chunkCol(C - 1), ((s - S0) * NP) / NS, ((s - S0 + 1) * NP) / NS>(c, prev, H);
        retire(c, (chunkSt0(C) + s + NST - 1) % NST);
        if constexpr (s == S0 - 1) reg_fence(prev);
        if constexpr (C == 2 && s == 0) { if (c.lead) mbar_arrive(c.bar + 8 * B_BXE); }
        chunk_loop<C, s + 1, S0>(c, acc, prev, H);
    }
}

template <int PAR, int s>
__device__ __forceinline__ void p2_stage(const Ctx& c, float (&acc)[32], const uint32_t (&H)[144]) {
    CWAIT(c.bar + 8 * (B_FULLW + s), PAR);
    wg_fence();
    sfor<0, 6>([&](auto kk) {
        constexpr int k = kk.v, h0 = s * 24 + 4 * k;
        WGrs<64>::template mma<0, 1, dlo(SM0 + W_OFF + s * W_ST + k * 2048, 0), dhi(1024, 1), (s | k) != 0>(acc, H[h0], H[h0 + 1], H[h0 + 2], H[h0 + 3], 0);
    });
    wg_commit();
}

template <int C>
__device__ __forceinline__ void phase1_rest(Ctx& c, float (&prev)[chunkN(C - 1) / 2], uint32_t (&H)[144], float (&accA)[32], uint32_t pe0Remote) {
    if constexpr (C < NCH) {
        DBG(9 + C);
        float acc[chunkN(C) / 2];
        chunk_loop<C, 0, 1>(c, acc, prev, H);
        phase1_rest<C + 1>(c, acc, H, accA, pe0Remote);
    } else {
        constexpr int NP = chunkN(C - 1) / 4, COL = chunkCol(C - 1);
        constexpr int NS = COL / 96 - 1;
        DBG(3); DBGT(62);
        sfor<0, 6>([&](auto ss) {
            constexpr int s = ss.v;
            p2_stage<1, s>(c, accA, H);
            if constexpr (s > 0 && s <= NS) gelu_range<COL, ((s - 1) * NP) / NS, (s * NP) / NS>(c, prev, H);
            retire(c, (s + 5) % 6);
            if constexpr (s == 0) {
                reg_fence(prev);
                if (c.lead) mbar_arrive_cluster(pe0Remote);
            }
        });
    }
}

__device__ __forceinline__ uint32_t bufoff(int b, int f) { return (((f >> 1) + 1 + b) & 3) * 16384; }
__device__ __forceinline__ uint32_t hadd2(uint32_t a, uint32_t b) { uint32_t r; asm("add.rn.bf16x2 %0, %1, %2;" : "=r"(r) : "r"(a), "r"(b)); return r; }

struct Maps { CUtensorMap w1[3], w2, h; };

__global__ void __launch_bounds__(384, 1) __cluster_dims__(2, 1, 1)
ffn_kernel(Scratch* __restrict__ sc, const bf16* __restrict__ b1, const bf16* __restrict__ w2, const bf16* __restrict__ b2, bf16* __restrict__ out, const __grid_constant__ Maps mp) {
    extern __shared__ __align__(1024) unsigned char smem_raw[];
    const uint32_t sb = s2u(smem_raw);
    if ((sb & 0xFFFFFF) != SM0) __trap();
    const uint32_t bar = sb + BAR_OFF;
    const int wid = __shfl_sync(0xffffffffu, threadIdx.x >> 5, 0);
    const int lane = threadIdx.x & 31;
    if (blockIdx.x < 4) {
        if (wid >= 8) return;
        const uint32_t par = (__ldcg(sc->epoch1) + 1) & 1;
        const int wg = wid >> 2, g0 = (blockIdx.x * 2 + wg) * 9;
        const uint32_t rb = wg * 110592;
        auto load = [&](int i) {
            const int b = i % 3;
#pragma unroll 1
            for (int s = 0; s < 3; s++) tma3d(sb + rb + b * 36864 + s * W_ST, &mp.w1[0], 0, (i & 1) * 288 + s * 96, g0 + (i >> 1), bar + 8 * (wg * 3 + b));
            mbar_expect(bar + 8 * (wg * 3 + b), 36864);
        };
        if ((wid & 3) < 3 && elect_one()) { mbar_init(bar + 8 * (wg * 3 + (wid & 3)), 1); load(wid & 3); }
        asm volatile("st.shared.b32 [%0], %1;" ::"r"(sb + BX_OFF + lane * 4), "r"(0x3f803f80u) : "memory");
        fence_async_smem();
        asm volatile("bar.sync %0, 128;" ::"r"(1 + wg) : "memory");
        const int cl = g0 * 64 + (wid & 3) * 16 + (lane >> 2) + (lane & 1) * 8;
        float acc[4] = {};
        uint32_t bv = 0;
#pragma unroll 1
        for (int i = 0; i < 18; i++) {
            if (!(i & 1)) bv = ((const unsigned short*)b1)[cl + (i >> 1) * 64];
            mbar_wait(bar + 8 * (wg * 3 + i % 3), (i / 3) & 1);
            const uint32_t la = (rb + (i % 3) * 36864) >> 4;
#pragma unroll 1
            for (int k = 0; k < 6; k++) {
                wg_fence();
                sfor<0, 3>([&](auto kk) { WGss<8>::template mma<0, 1, 0, dlo(SM0 + kk.v * 2048, 0), dhi(1024, 1), dlo(SM0 + BX_OFF, 0), dhi(0, 0), 1>(acc, la + k * 384, 0); });
            }
            wg_commit();
            wg_wait<0>();
            reg_fence(acc);
            asm volatile("bar.sync %0, 128;" ::"r"(1 + wg) : "memory");
            if ((wid & 3) == 1 && i + 3 < 18 && elect_one()) load(i + 3);
            if (i & 1) {
                const float cs = (lane & 1) ? acc[2] : acc[0], ch = bf_round(cs), cm = bf_round(cs - ch);
                if (!(lane & 2)) st_tagged(sc->bx + cl + (i >> 1) * 64, pack_bf16(cs - ch - cm, ch), pack_bf16(ch, ch), pack_bf16(cm, cm), bv * 0x10001u, par);
                acc[0] = acc[1] = acc[2] = acc[3] = 0.f;
            }
        }
        return;
    }
    const int bid = blockIdx.x - 4;
    const int m = bid >> 3, f = bid & 7, r = f & 1;
    DBG(0); DBGT(60);
    auto loadW0 = [&](int s) {
        constexpr int N = chunkN(0);
        tma3d(sb + W_OFF + s * W_ST, &mp.w1[N / 32 - 2], 0, s * chunkKS(0), N == 96 ? f * 18 : f * 9, bar + 8 * (B_FULLW + s));
        mbar_expect(bar + 8 * (B_FULLW + s), W_ST);
    };
    auto loadA = [&](int i) {
        tma2d(sb + A_OFF + i * 8192, &mp.h, m * 128, i * 64, bar + 8 * (B_FULLA + i));
        tma2d(sb + A_OFF + A_WG + i * 8192, &mp.h, m * 128 + 64, i * 64, bar + 8 * (B_FULLA + i));
        mbar_expect(bar + 8 * (B_FULLA + i), 16384);
    };
    if (elect_one()) {
        if (wid >= 8) asm volatile("prefetch.tensormap [%0];" ::"l"(wid == 11 ? &mp.h : wid == 10 ? &mp.w2 : &mp.w1[wid - 8]) : "memory");
        mbar_init(bar + 8 * wid, wid < B_EMPTYW ? 1 : 8);
        if (wid < NW0) loadW0(wid);
        if (wid >= 3) mbar_init(bar + 8 * (B_FULLA + wid - 3), 1);
    }
    asm volatile("bar.sync 0;" ::: "memory");

    if (wid >= 8) {
        asm volatile("setmaxnreg.dec.sync.aligned.u32 24;");
        if (wid == 8) {
            asm volatile("barrier.cluster.arrive.relaxed.aligned;" ::: "memory");
            if (elect_one()) {
#pragma unroll 1
                for (int s = NW0; s < NW1; s++) loadW0(s);
                asm volatile("griddepcontrol.wait;" ::: "memory");
#pragma unroll 1
                for (int i = NA0, s = NW1, pat = LPAT; i < 9 || s < NST; pat >>= 1) { if (pat & 1) loadA(i++); else loadW0(s++); }
            }
            __syncwarp();
            int slot = 0, par = 0, k = NST * chunkKS(0);
#pragma unroll 1
            for (int C = 0; C < NCH; C++) {
                const int n32 = (packTab(0) >> (8 * C)) & 255, c32 = (packTab(1) >> (8 * C)) & 255;
                const int ks = n32 == 2 ? 96 : n32 == 3 ? 64 : 48, g = n32 == 3 ? f * 18 + c32 : f * 9 + (c32 >> 1);
#pragma unroll 1
                for (; k < 576; k += ks) {
                    mbar_wait(bar + 8 * (B_EMPTYW + slot), par);
                    if (elect_one()) {
                        tma3d(sb + W_OFF + slot * W_ST, &mp.w1[n32 - 2], 0, k, g, bar + 8 * (B_FULLW + slot));
                        mbar_expect(bar + 8 * (B_FULLW + slot), W_ST);
                    }
                    if (++slot == NST) { slot = 0; par ^= 1; }
                }
                k = 0;
            }
#pragma unroll 1
            for (int p = 0; p < 9; p++) {
                const int blk = p == 0 ? 8 : 2 * (((f >> 1) + ((p + 1) >> 1)) & 3) + ((p & 1) ^ r);
#pragma unroll 1
                for (int s = 0; s < 6; s++) {
                    mbar_wait(bar + 8 * (B_EMPTYW + s), p & 1);
                    if (elect_one()) {
                        tma2d(sb + W_OFF + s * W_ST, &mp.w2, blk * 64, f * 576 + s * 96, bar + 8 * (B_FULLW + s));
                        mbar_expect(bar + 8 * (B_FULLW + s), W_ST);
                    }
                }
            }
            if (LEAN) mbar_wait(bar + 8 * B_DONE, 0);
        } else {
            const int hw = wid - 9;
            if (elect_one()) {
#pragma unroll 1
                for (int i = B_PFULL + hw; i < B_N; i += 3) {
                    mbar_init(bar + 8 * i, i >= B_P1D ? 8 : (i == B_PE || i == B_PE + 1) ? 4 : i == B_Z ? 3 : i == B_STAT ? 2 : 1);
                    if (i < B_PE) mbar_expect(bar + 8 * i, 8192);
                }
                asm volatile("fence.mbarrier_init.release.cluster;" ::: "memory");
            }
            __syncwarp();
            asm volatile("barrier.cluster.arrive.relaxed.aligned;" ::: "memory");
            asm volatile("griddepcontrol.wait;" ::: "memory");
            DBGH(hw == 0 ? 30 : 31);
            const unsigned ep = __ldcg(sc->epoch);
            const uint32_t bb2 = *(const uint32_t*)(b2 + (hw == 2 ? 512 : f * 64) + 2 * lane);
            if (hw == 0) {
#pragma unroll
                for (int i = 0; i < chunkN(0) / 32; i++) cp16(sb + BX_OFF + i * 512 + lane * 16, sc->bx + f * 576 + i * 32 + lane);
            }
            {
                const int q = lane & 3, ds = ((lane >> 1) & 6) | (lane >> 4);
                const uint32_t la = sb + A_OFF + (f >> 2) * A_WG + ds * 128 + (((2 * (f & 3) + (q >> 1)) ^ ds) << 4) + (q & 1) * 8;
                float v[8];
#pragma unroll
                for (int i = 0; i < 8; i++) v[i] = 0.f;
#pragma unroll 1
                for (int i = 0; i < 8; i++) {
                    mbar_wait(bar + 8 * (B_FULLA + i + 1), 0);
                    if (i == 0) mbar_wait(bar + 8 * B_FULLA, 0);
                    if (hw == 2 && i == 7) DBGH(41);
                    if (hw == 2 && i == 0) DBGH(40);
#pragma unroll
                    for (int j = 0; j < 3; j++) {
                        uint32_t w0, w1;
                        asm volatile("ld.shared.v2.b32 {%0,%1}, [%2];" : "=r"(w0), "=r"(w1) : "r"(la + (i * 9 + j * 3 + hw) * 1024));
                        const float a0 = bf_lo(w0), a1 = bf_hi(w0), a2 = bf_lo(w1), a3 = bf_hi(w1);
                        v[0] += a0; v[1] += a1; v[2] += a2; v[3] += a3;
                        v[4] = fmaf(a0, a0, v[4]); v[5] = fmaf(a1, a1, v[5]); v[6] = fmaf(a2, a2, v[6]); v[7] = fmaf(a3, a3, v[7]);
                    }
                }
                if (hw == 2) DBGH(42);
                const bool b4 = lane & 16, b3 = lane & 8, b2_ = lane & 4;
#pragma unroll
                for (int i = 0; i < 4; i++) v[i] = (b4 ? v[4 + i] : v[i]) + __shfl_xor_sync(0xffffffffu, b4 ? v[i] : v[4 + i], 16);
#pragma unroll
                for (int i = 0; i < 2; i++) v[i] = (b3 ? v[2 + i] : v[i]) + __shfl_xor_sync(0xffffffffu, b3 ? v[i] : v[2 + i], 8);
                v[0] = (b2_ ? v[1] : v[0]) + __shfl_xor_sync(0xffffffffu, b2_ ? v[0] : v[1], 4);
                if (hw < 2) {
                    asm volatile("st.shared.f32 [%0], %1;" ::"r"(sb + ST_OFF + hw * 128 + lane * 4), "f"(v[0]) : "memory");
                }
                asm volatile("bar.sync 1, 96;" ::: "memory");
                if (hw == 2) {
                    const float t = (v[0] + lds32f(sb + ST_OFF + lane * 4) + lds32f(sb + ST_OFF + 128 + lane * 4)) * (1.f / D_);
                    const float sq = __shfl_xor_sync(0xffffffffu, t, 16);
                    if (!b4) {
                        const float hs = 0.5f * sqrt_fast(fmaxf(sq - t * t, 0.f) + 1e-5f), nm = -0.5f * t;
                        const float sh = bf_round(hs), mh = bf_round(nm), ml = bf_round(nm - mh);
                        const uint32_t mm = pack_bf16(mh, ml);
                        st_tagged(sc->st2 + m * 128 + f * 16 + 4 * q + ((lane >> 2) & 3), pack_bf16(mh, nm - mh - ml), mm, mm, pack_bf16(sh, hs - sh), ep & 1);
                    }
                }
            }
            if (hw == 2) DBGH(43);
            const uint32_t par = __shfl_sync(0xffffffffu, ep & 1, 0);
            if (hw > 0) {
                uint4 st[2];
#pragma unroll 1
                for (int it = 0; it < 4000000; it++) {
                    st[0] = ld_tagged<0>(sc->st2 + m * 128 + (hw - 1) * 64 + lane);
                    st[1] = ld_tagged<32>(sc->st2 + m * 128 + (hw - 1) * 64 + lane);
                    if (!__any_sync(0xffffffffu, tagbad(st[0].x, st[1].x, par) & 1)) break;
                }
                if (hw == 2) DBGH(44);
#pragma unroll
                for (int i = 0; i < 2; i++) {
                    sts128u(sb + AX_OFF + ((hw - 1) * 64 + i * 32 + lane) * 16, st[i].x, st[i].y, st[i].z, st[i].w);
                    asm volatile("st.shared.f32 [%0], %1;" ::"r"(sb + RS_OFF + ((hw - 1) * 64 + i * 32 + lane) * 4), "f"(0.25f * rcp_fast(bf_lo(st[i].w) + bf_hi(st[i].w))) : "memory");
                }
                asm volatile("st.shared.v2.f32 [%0], {%1, %2};" ::"r"(sb + B2_OFF + (hw - 1) * 256 + lane * 8), "f"(bf_lo(bb2)), "f"(bf_hi(bb2)) : "memory");
                if (lane == 0) asm volatile("st.shared.b32 [%0], %1;" ::"r"(sb + BAR_OFF + 504), "r"(par) : "memory");
                fence_async_smem();
                __syncwarp();
                if (lane == 0) mbar_arrive(bar + 8 * B_STAT);
                if (hw == 2) DBGH(45);
                if (hw == 1 && lane < 9)
                    asm volatile("cp.async.bulk.prefetch.L2.global [%0], %1;" ::"l"(w2 + (size_t)(f * 576 + m * 36 + lane * 4) * 576), "r"(4608) : "memory");
            } else {
#pragma unroll 1
                for (int C = 0; C < NCH; C++) {
                    const int n32 = (packTab(0) >> (8 * C)) & 255;
                    const uint4* g = sc->bx + f * 576 + ((packTab(1) >> (8 * C)) & 255) * 32 + lane;
                    const uint32_t a = sb + BX_OFF + ((packTab(2) >> (8 * C)) & 255) * 512 + lane * 16;
                    if (C == bxWrap()) mbar_doze(bar + 8 * B_BXE);
#pragma unroll 1
                    for (int it = 0; it < 4000000; it++) {
                        if (C | it) {
#pragma unroll 1
                            for (int i = 0; i < n32; i++) cp16(a + i * 512, g + i * 32);
                        }
                        asm volatile("cp.async.wait_all;" ::: "memory");
                        const uint32_t bad = tagbad(lds32u(a), lds32u(a + 512), par) | tagbad(lds32u(a + (n32 - 2) * 512), lds32u(a + (n32 - 1) * 512), par);
                        if (!__any_sync(0xffffffffu, bad & 1)) break;
                        __nanosleep(200);
                    }
                    fence_async_smem();
                    __syncwarp();
                    if (lane == 0) mbar_arrive(bar + 8 * (B_BXF + C));
                    if (C < 3) DBGH(46 + C);
                }
            }
            uint32_t lm = (lane & 7) * 128 + ((((lane >> 3) & 1) ^ (lane & 7)) << 4);
            uint32_t tq = sb + (lane & 3) * 8, tg = sb + (lane >> 2) * 4;
            asm volatile("" : "+r"(lm), "+r"(tq), "+r"(tg));
            if (DOZE) mbar_doze(bar + 8 * B_P1D); else mbar_wait(bar + 8 * B_P1D, 0);
            DBGH((hw & 1) * 64 + 26);
            const uint32_t yb = sb + A_OFF + bufoff(2, f) + lane * 16;
#pragma unroll 1
            for (int w = hw; w < 8; w += 3) {
                const uint32_t ha = sb + A_OFF + (w >> 2) * A_WG + f * 8192 + (lm ^ ((w & 3) << 5));
                const uint32_t ya = yb + (w >> 2) * A_WG + (w & 3) * 512;
#pragma unroll 1
                for (int j = 0; j < 8; j++) {
                    uint32_t h0, h1;
                    asm volatile("ldmatrix.sync.aligned.m8n8.x2.trans.shared.b16 {%0,%1}, [%2];" : "=r"(h0), "=r"(h1) : "r"(ha + j * 1024));
                    float b0, b1;
                    asm volatile("ld.shared.v2.f32 {%0,%1}, [%2];" : "=f"(b0), "=f"(b1) : "r"(tq + B2_OFF + j * 32));
                    sts128f(ya + j * 2048, bf_lo(h0) + b0, bf_hi(h0) + b1, bf_lo(h1) + b0, bf_hi(h1) + b1);
                }
            }
            DBGH((hw & 1) * 64 + 27);
            const uint32_t ring = sb + A_OFF + (hw >> 1) * A_WG + bufoff(1, f) + (hw & 1) * 8192 + lane * 16;
#pragma unroll 1
            for (int d = hw; d <= 4; d = hw == 2 ? d + 1 : d < 4 ? 4 : 5) {
                const bool p1 = d == 4;
                const int n = p1 && hw < 2 ? 12 : 8, s4 = p1 ? 384 : 4096, s1 = p1 ? 32 : 1024;
                const uint4* g = sc->part + (size_t)(m * 8) * 1024 + (p1 ? (128 + f) * 1024 + hw * 128 : f * 128 + d * 32) + lane;
                if (DOZE) mbar_doze(bar + 8 * (B_TICK + p1)); else mbar_wait(bar + 8 * (B_TICK + p1), 0);
#pragma unroll 1
                for (int it = 0; it < 1000000; it++) {
#pragma unroll 1
                    for (int i = 0; i < n; i++) cp16(ring + i * 512, g + (i >> 2) * s4 + (i & 3) * s1);
                    asm volatile("cp.async.wait_all;" ::: "memory");
                    uint32_t bad = 0;
#pragma unroll 1
                    for (int i = 0; i < n; i += 2) bad |= tagbad(lds32u(ring + i * 512), lds32u(ring + i * 512 + 512), par);
                    if (!__any_sync(0xffffffffu, bad & 1)) break;
                }
                if (p1) {
#pragma unroll 1
                    for (int i = 0; i < n; i++) {
                        const int w = hw + (i >> 2) * 3;
                        const float r0 = lds32f(tg + RS_OFF + w * 64), r1 = lds32f(tg + RS_OFF + w * 64 + 32);
                        const uint32_t ya = yb + (w >> 2) * A_WG + (w & 3) * 512 + (i & 3) * 4096;
                        const uint4 v = lds128u(ring + i * 512);
                        const float4 y0 = lds128f(ya), y1 = lds128f(ya + 2048);
                        sts128f(ya, fmaf(bf_lo(v.x), r0, y0.x), fmaf(bf_hi(v.x), r0, y0.y), fmaf(bf_lo(v.y), r1, y0.z), fmaf(bf_hi(v.y), r1, y0.w));
                        sts128f(ya + 2048, fmaf(bf_lo(v.z), r0, y1.x), fmaf(bf_hi(v.z), r0, y1.y), fmaf(bf_lo(v.w), r1, y1.z), fmaf(bf_hi(v.w), r1, y1.w));
                    }
                } else {
#pragma unroll 1
                    for (int u = 0; u < 2; u++) {
                        float a0 = 0.f, a1 = 0.f, a2 = 0.f, a3 = 0.f;
#pragma unroll 2
                        for (int i = 0; i < 8; i++) {
                            uint32_t v0, v1;
                            asm volatile("ld.shared.v2.b32 {%0,%1}, [%2];" : "=r"(v0), "=r"(v1) : "r"(ring + i * 512 + u * 8));
                            a0 += bf_lo(v0); a1 += bf_hi(v0); a2 += bf_lo(v1); a3 += bf_hi(v1);
                        }
                        const float r0 = lds32f(tg + RS_OFF + f * 64), r1 = lds32f(tg + RS_OFF + f * 64 + 32);
                        uint32_t h0, h1;
                        asm volatile("ldmatrix.sync.aligned.m8n8.x2.trans.shared.b16 {%0,%1}, [%2];" : "=r"(h0), "=r"(h1)
                                     : "r"(sb + A_OFF + (f >> 2) * A_WG + 8 * 8192 + (2 * d + u) * 1024 + (lm ^ ((f & 3) << 5))));
                        float b0, b1;
                        asm volatile("ld.shared.v2.f32 {%0,%1}, [%2];" : "=f"(b0), "=f"(b1) : "r"(tq + B2_OFF + 256 + (2 * d + u) * 32));
                        bf16* o = out + (size_t)(m * 128 + f * 16 + (lane >> 2)) * D_ + 512 + 16 * d + 8 * u + 2 * (lane & 3);
                        *(uint32_t*)o = pack_bf16(fmaf(a0, r0, bf_lo(h0) + b0), fmaf(a1, r0, bf_hi(h0) + b1));
                        *(uint32_t*)(o + 8 * D_) = pack_bf16(fmaf(a2, r1, bf_lo(h1) + b0), fmaf(a3, r1, bf_hi(h1) + b1));
                    }
                }
                DBGH((hw & 1) * 64 + 28 + p1);
            }
            if (bid == 0 && threadIdx.x == 288) sc->epoch1[0] = __ldcg(sc->epoch);
            __syncwarp();
            if (lane == 0) mbar_arrive(bar + 8 * B_Z);
        }
    } else {
        asm volatile("setmaxnreg.inc.sync.aligned.u32 240;");
        asm volatile("barrier.cluster.arrive.relaxed.aligned;" ::: "memory");
        Ctx c;
        const int wg = wid >> 2, warp = wid & 3;
        c.bar = bar; c.lead = lane == 0; c.go = gridDim.y;
        c.aD = wg * (A_WG >> 4); c.xD = wg * 64;
        uint32_t H[144];
        float accA[32], accB[32];
        {
            float acc0[chunkN(0) / 2], acc1[chunkN(1) / 2];
#pragma unroll
            for (int i = 0; i < chunkN(0) / 2; i++) acc0[i] = 0.f;
            DBG(1);
            chunk0(c, acc0);
            asm volatile("barrier.cluster.wait.aligned;" ::: "memory");
            DBG(2);
            sfor<0, AUGD + 1>([&](auto ss) {
                constexpr int s = ss.v;
                if constexpr (s == AUGD) { CWAIT(bar + 8 * B_BXF, 0); CWAIT(bar + 8 * B_STAT, 0); DBG(17); }
                p1_mma<1, s>(c, acc1);
                if constexpr (s == AUGD) aug_mma<0>(c, acc0);
                wg_commit();
                retire(c, (chunkSt0(1) + s + NST - 1) % NST);
            });
            const float r0 = lds32f(sb + RS_OFF + (wid * 16 + (lane >> 2)) * 4), r1 = lds32f(sb + RS_OFF + (wid * 16 + 8 + (lane >> 2)) * 4);
            c.k00 = (2.0f * 0.7978845608028654f) * r0; c.k01 = (2.0f * 0.7978845608028654f) * r1;
            c.k10 = (4.0f * 0.044715f) * c.k00 * r0 * r0; c.k11 = (4.0f * 0.044715f) * c.k01 * r1 * r1;
            chunk_loop<1, AUGD + 1, AUGD + 2>(c, acc1, acc0, H);
            phase1_rest<2>(c, acc1, H, accA, mapa(bar + 8 * (B_PE + wg), r ^ 1));
        }
        DBG(4);
        const uint32_t par = __shfl_sync(0xffffffffu, __float_as_uint(lds32f(sb + BAR_OFF + 504)), 0);
        uint32_t sl = sb + A_OFF + wg * A_WG + warp * 512 + lane * 16;
        uint4* gp = sc->part + (size_t)(m * 8) * 1024 + wid * 128 + lane;
        asm volatile("" : "+r"(sl), "+l"(gp));
        if (c.lead) mbar_arrive(bar + 8 * B_P1D);
        const uint4* p2 = gp + (2 * 128 + f) * 1024;
        auto load23 = [&]() {
            sfor<0, 8>([&](auto dd) {
                constexpr int d = dd.v;
                const uint4 v = ld_tagged<(d >> 2) * 128 * 1024 + (d & 3) * 32>(p2);
                accB[4 * d] = __uint_as_float(v.x); accB[4 * d + 1] = __uint_as_float(v.y); accB[4 * d + 2] = __uint_as_float(v.z); accB[4 * d + 3] = __uint_as_float(v.w);
            });
        };
#pragma unroll 1
        for (int I = 1; I <= 4; I++) {
            const uint32_t la = sl + bufoff(0, f) + (I & 1) * 8192;
            uint4* o = gp + ((I - 1) * 128 + ((f + 2 * I - 2) & 7)) * 1024;
            uint4 v = make_uint4(0, 0, 0, 0);
            p2_stage<0, 0>(c, accB, H);
            retire(c, 5);
            reg_fence(accA);
            CWAIT(bar + 8 * (I > 1 ? B_PFULL + wg * 4 + I - 2 : B_PE + wg), 0);
            if (I > 1) v = lds128u(la);
            sfor<0, 4>([&](auto dd) {
                constexpr int d = dd.v, k = 8 * d;
                p2_stage<0, 1 + d>(c, accB, H);
                retire(c, d);
                const uint32_t x = hadd2(pack_bf16(accA[k], accA[k + 1]), v.x), y = hadd2(pack_bf16(accA[k + 2], accA[k + 3]), v.y);
                const uint32_t z = hadd2(pack_bf16(accA[k + 4], accA[k + 5]), v.z), w = hadd2(pack_bf16(accA[k + 6], accA[k + 7]), v.w);
                if (d < 3 && I > 1) v = lds128u(la + (d + 1) * 2048);
                st_tagged(o + d * 32, x, y, z, w, par);
            });
            p2_stage<0, 5>(c, accB, H);
            retire(c, 4);
            DBG(20);
            const uint32_t dst = mapa(sl + bufoff(0, f) + ((I - 1) & 1) * 8192, r ^ 1);
            const uint32_t pf = mapa(bar + 8 * (B_PFULL + wg * 4 + I - 1), r ^ 1);
            sfor<0, 6>([&](auto dd) {
                constexpr int d = dd.v, k = 8 * (d & 3);
                p2_stage<1, d>(c, accA, H);
                retire(c, (d + 5) % 6);
                if constexpr (d == 0) { reg_fence(accB); if (c.lead && I < 3) mbar_arrive(bar + 8 * (B_TICK + I - 1)); }
                if constexpr (d < 4)
                    asm volatile("st.async.weak.shared::cluster.mbarrier::complete_tx::bytes.v4.b32 [%0], {%1,%2,%3,%4}, [%5];" ::"r"(dst + d * 2048),
                                 "r"(pack_bf16(accB[k], accB[k + 1])), "r"(pack_bf16(accB[k + 2], accB[k + 3])), "r"(pack_bf16(accB[k + 4], accB[k + 5])),
                                 "r"(pack_bf16(accB[k + 6], accB[k + 7])), "r"(pf) : "memory");
                if constexpr (d == 3) { if (I == 4) load23(); }
            });
            DBG(4 + I);
        }
        DBG(22);
        const uint32_t yb = sl + bufoff(2, f);
        const float r0 = lds32f(sb + RS_OFF + (wid * 16 + (lane >> 2)) * 4), r1 = lds32f(sb + RS_OFF + (wid * 16 + 8 + (lane >> 2)) * 4);
        CWAIT(bar + 8 * B_Z, 0);
        CWAIT(bar + 8 * (B_PFULL + wg * 4 + 3), 0);
        if (LEAN && c.lead) mbar_arrive(bar + 8 * B_DONE);
        float4 y[8];
        uint4 pe[4];
#pragma unroll
        for (int d = 0; d < 4; d++) pe[d] = lds128u(sl + bufoff(0, f) + 8192 + d * 2048);
#pragma unroll
        for (int j = 0; j < 8; j++) y[j] = lds128f(yb + j * 2048);
#pragma unroll 1
        for (int it = 0; it < 1000000; it++) {
            uint32_t bad = 0;
#pragma unroll
            for (int d = 0; d < 8; d += 2) bad |= tagbad(__float_as_uint(accB[4 * d]), __float_as_uint(accB[4 * d + 4]), par);
            if (!__any_sync(0xffffffffu, bad & 1)) break;
            load23();
        }
        DBG(25);
        wg_wait<0>();
        reg_fence(accA);
        DBG(9);
        const int rq = (lane & 7) + ((lane >> 3) & 1) * 8;
        const uint32_t sa = yb - lane * 16 + (rq >> 2) * 2048 + (rq & 3) * 128 + (((lane >> 4) ^ (lane & 7)) << 4);
        const uint32_t lda = yb - lane * 16 + (lane >> 3) * 128 + (((lane & 7) ^ (lane >> 3)) << 4);
        bf16* op = out + (size_t)(m * 128 + wid * 16 + (lane >> 3)) * D_ + f * 64 + (lane & 7) * 8;
#pragma unroll
        for (int d = 0; d < 4; d++) {
            const uint32_t pw[4] = {pe[d].x, pe[d].y, pe[d].z, pe[d].w};
            const float yy[8] = {y[2 * d].x, y[2 * d].y, y[2 * d].z, y[2 * d].w, y[2 * d + 1].x, y[2 * d + 1].y, y[2 * d + 1].z, y[2 * d + 1].w};
            uint32_t q[4];
#pragma unroll
            for (int i = 0; i < 4; i++) {
                const uint32_t x = hadd2(hadd2(__float_as_uint(accB[4 * d + i]), pw[i]), __float_as_uint(accB[16 + 4 * d + i]));
                const float rs = (i & 1) ? r1 : r0;
                q[i] = pack_bf16(fmaf(accA[8 * d + 2 * i] + bf_lo(x), rs, yy[2 * i]), fmaf(accA[8 * d + 2 * i + 1] + bf_hi(x), rs, yy[2 * i + 1]));
            }
            asm volatile("stmatrix.sync.aligned.m8n8.x4.shared.b16 [%0], {%1,%2,%3,%4};" ::"r"(sa ^ (d << 5)), "r"(q[0]), "r"(q[1]), "r"(q[2]), "r"(q[3]) : "memory");
        }
        __syncwarp();
#pragma unroll
        for (int i = 0; i < 4; i++) *(uint4*)(op + i * 4 * D_) = lds128u((lda ^ ((i & 1) << 6)) + i * 2048);
        DBG(10); DBGT(63);
    }
}
}

namespace cv {
constexpr int SUNR = SUNR_;
constexpr int KV_UNIT = 12800, V_REL = 7040;
constexpr int KV_OFF = 0;
constexpr int XS_OFF = 51200;
constexpr int W_OFF = 71680, W_PITCH = 8448;
constexpr int K_OFF = 113920, K_PITCH = 4368;
constexpr int XT_OFF = 135808;
constexpr int Z_OFF = 156288, Z_ARR = 4224, Z_SET = 4 * Z_ARR;
constexpr int XR_OFF = 190464;
constexpr int CF_OFF = 208896;
constexpr int BAR_OFF = 209344;
constexpr int XO_OFF = 209600, XO_PITCH = 2624;
constexpr int SMEM = XO_OFF + 7 * XO_PITCH;
static_assert(3 * Z_SET <= XS_OFF, "");
constexpr int B_LD = 0, B_KF = 4, B_LX = 7, B_UF = 8, B_UF2 = 12, B_XF = 14, B_LR = 15, B_KR = 16, B_ZF = 19, B_ACK = 29, B_N = 30;

__device__ __forceinline__ uint32_t hmul2(uint32_t a, uint32_t b) { uint32_t r; asm("mul.rn.bf16x2 %0, %1, %2;" : "=r"(r) : "r"(a), "r"(b)); return r; }
__device__ __forceinline__ uint32_t hadd2(uint32_t a, uint32_t b) { uint32_t r; asm("add.rn.bf16x2 %0, %1, %2;" : "=r"(r) : "r"(a), "r"(b)); return r; }
__device__ __forceinline__ uint32_t hsub2(uint32_t a, uint32_t b) { uint32_t r; asm("sub.rn.bf16x2 %0, %1, %2;" : "=r"(r) : "r"(a), "r"(b)); return r; }
__device__ __forceinline__ uint32_t hfma2(uint32_t a, uint32_t b, uint32_t c) { uint32_t r; asm("fma.rn.bf16x2 %0, %1, %2, %3;" : "=r"(r) : "r"(a), "r"(b), "r"(c)); return r; }
__device__ __forceinline__ void ldsm4t(uint32_t* r, uint32_t a) {
    asm volatile("ldmatrix.sync.aligned.m8n8.x4.trans.shared.b16 {%0,%1,%2,%3}, [%4];" : "=r"(r[0]), "=r"(r[1]), "=r"(r[2]), "=r"(r[3]) : "r"(a));
}
__device__ __forceinline__ void stas4(uint32_t a, uint32_t x, uint32_t y, uint32_t z, uint32_t w, uint32_t mb) {
    asm volatile("st.async.weak.shared::cluster.mbarrier::complete_tx::bytes.v4.b32 [%0], {%1,%2,%3,%4}, [%5];" ::"r"(a), "r"(x), "r"(y), "r"(z), "r"(w), "r"(mb) : "memory");
}
__device__ __forceinline__ int wpos(int x) { const int j = (x >> 2) & 3, t = (x >> 4) & 3; return ((x & ~63) + 16 * j + 4 * (t ^ (j & 2)) + (x & 3)) * 4; }
__device__ __forceinline__ uint32_t zbase(uint32_t sb, int slot) { return sb + (slot < 2 ? Z_OFF + slot * Z_SET : KV_OFF + (slot - 2) * Z_SET); }

template <int P>
__device__ __forceinline__ void load_a(uint32_t (&a)[8], uint32_t w0, uint32_t w8) {
#pragma unroll
    for (int i = 0; i < 2; i++) {
        a[4 * i] = lds32u(w8 + (2 * P + i) * 512); a[4 * i + 1] = lds32u(w8 + (2 * P + i) * 512 + 256);
        a[4 * i + 2] = lds32u(w0 + (2 * P + i) * 512); a[4 * i + 3] = lds32u(w0 + (2 * P + i) * 512 + 256);
    }
}
template <int P>
__device__ __forceinline__ void retire_cols(float (&acc)[16], float& c0, float& c1, uint32_t za) {
    uint32_t q[4];
    reg_fence(acc);
#pragma unroll
    for (int i = 0; i < 4; i++) {
        q[i] = pack_bf16(acc[4 * i] + c0, acc[4 * i + 1] + c1);
        c0 = acc[4 * i + 2]; c1 = acc[4 * i + 3];
    }
    asm volatile("stmatrix.sync.aligned.m8n8.x4.trans.shared.b16 [%0], {%1,%2,%3,%4};" ::"r"(za + P * 512), "r"(q[0]), "r"(q[1]), "r"(q[2]), "r"(q[3]) : "memory");
}
template <int P, int C0, int N, int SD>
__device__ __forceinline__ void pair_mma(float (&acc)[N / 2], const uint32_t (&a)[8], uint32_t kd) {
    WGrs<N>::template mma<0, 0, dlo(SM0 + K_OFF + 256 + 16 * (C0 - 32 * P), 16), dhi(128, 0), SD>(acc, a[0], a[1], a[2], a[3], kd);
    WGrs<N>::template mma<0, 0, dlo(SM0 + K_OFF + 16 * (C0 - 32 * P), 16), dhi(128, 0), 1>(acc, a[4], a[5], a[6], a[7], kd);
}
__device__ __forceinline__ void conv_slot(uint32_t sb, int slot, int warp, int lane, int go) {
    const uint32_t bar = sb + BAR_OFF;
    const int o = 16 * warp + (lane >> 2) - 2 * (lane & 3);
    const uint32_t wb = sb + W_OFF + slot * W_PITCH + 256;
    const uint32_t w0 = wb + wpos(o), w8 = wb + wpos(o + 8);
    const uint32_t za = zbase(sb, slot) + warp * (Z_ARR + 32) + lane * 16;
    const uint32_t kd = slot * (K_PITCH >> 4);
    const uint32_t ub = bar + 8 * (slot < 2 ? B_UF : B_UF2 + (slot >> 2)), us = slot < 2 ? 8 : 0;
    float blk[8][16], accL[64], c0 = 0.f, c1 = 0.f;
    uint32_t a[3][8];
    mbar_spin(bar + 8 * (B_KR + (slot >> 1)), 0, go);
    if (lane < 2 * warp) sts128u(za - warp * 32, 0, 0, 0, 0);
    mbar_spin(ub, 0, go);
    if (slot < 2) DBG(2);
    load_a<0>(a[0], w0, w8);
    load_a<1>(a[1], w0, w8);
    if (SKEW && slot == 3) asm volatile("bar.sync 2, 256;" ::: "memory");
    sfor<0, 8>([&](auto pp) {
        constexpr int p = pp.v;
        if constexpr (p == 4) {
            wg_wait<0>();
#pragma unroll
            for (int i = 0; i < 64; i++) asm volatile("mov.b32 %0, %1;" : "=f"(blk[4 + i / 16][i % 16]) : "f"(accL[i]) : "memory");
        }
        wg_fence();
        sfor<p, (p < 4 ? 4 : 8)>([&](auto bb) { pair_mma<p, 32 * bb.v, 32, p != 0>(blk[bb.v], a[p % 3], kd); });
        if constexpr (p < 4) pair_mma<p, 128, 128, p != 0>(accL, a[p % 3], kd);
        wg_commit();
        if constexpr (p == SKEW - 1) { if (slot == 2) asm volatile("bar.arrive 2, 256;" ::: "memory"); }
        if constexpr (p > 0 && p != 4) wg_wait<1>();
        if constexpr ((p & 1) && p < 7) {
            mbar_spin(ub + us * ((p + 1) / 2), 0, go);
            load_a<p + 1>(a[(p + 1) % 3], w0, w8);
            load_a<p + 2>(a[(p + 2) % 3], w0, w8);
        }
        if constexpr (p > 0) retire_cols<p - 1>(blk[p - 1], c0, c1, za);
        if constexpr (p == 4) { __syncwarp(); if (lane == 0) mbar_arrive(bar + 8 * (B_ZF + slot * 2)); }
    });
    wg_wait<0>();
    retire_cols<7>(blk[7], c0, c1, za);
    __syncwarp();
    if (lane == 0) mbar_arrive(bar + 8 * (B_ZF + slot * 2 + 1));
    DBG(slot < 2 ? 4 : slot < 4 ? 7 : 22);
}

struct Maps { CUtensorMap x; };

__global__ void __launch_bounds__(512, 1) __cluster_dims__(8, 1, 1)
conv_kernel(const bf16* __restrict__ kin, const bf16* __restrict__ vin, const bf16* __restrict__ filt, const bf16* __restrict__ sk,
            const bf16* __restrict__ Dv, Scratch* __restrict__ sc, const bf16* __restrict__ x, const bf16* __restrict__ w1, const __grid_constant__ Maps mp) {
    extern __shared__ __align__(1024) unsigned char smem_raw[];
    const uint32_t sb = s2u(smem_raw);
    const uint32_t bar = sb + BAR_OFF;
    const int cl = blockIdx.x >> 3, rank = blockIdx.x & 7, c0 = cl * 40;
    const int ns = cl == 14 ? 2 : 5;
    DBG(0); DBGT(30);
    const int wid = __shfl_sync(0xffffffffu, threadIdx.x >> 5, 0);
    const int lane = threadIdx.x & 31, wg = wid >> 2, warp = wid & 3;
    if ((sb & 0xFFFFFF) != SM0) __trap();
    if (wg < 2) {
        const int id = threadIdx.x, q5 = id / 5, cg = id - q5 * 5, row = rank * 64 + (q5 & 3) * 16 + (q5 >> 2);
        const int off = row * D_ + c0 + (cg < ns ? cg * 8 : 0);
        const bf16 *kp = kin + off, *vp = vin + off;
        uint32_t d = sb + KV_OFF + id * 16;
        if (wid == 7 && lane < 26 && (lane < 4 * ns || lane >= 20) && (lane < 20 + ns || lane == 25))
            cp16(sb + CF_OFF + lane * 16, lane < 20 ? (const void*)(sk + (c0 + 2 * lane) * 4) : lane < 25 ? (const void*)(Dv + c0 + 8 * (lane - 20)) : (const void*)sc->epoch1);
#pragma unroll 1
        for (int c = 0; c < 4; c++, kp += 512 * D_, vp += 512 * D_, d += KV_UNIT) {
            const bool kz = c == 0 && row < 6, vz = c == 0 && row < 2;
            if (id < 240) {
                asm volatile("cp.async.cg.shared.global [%0], [%1], 16, %2;" ::"r"(d), "l"(kz ? kp : kp - 6 * D_), "r"(kz ? 0 : 16) : "memory");
                asm volatile("cp.async.cg.shared.global [%0], [%1], 16, %2;" ::"r"(d + V_REL), "l"(vz ? vp : vp - 2 * D_), "r"(vz ? 0 : 16) : "memory");
            }
            if (id < 200) cp16(d + 3840, kp + 6 * D_);
            if (id < 120) cp16(d + V_REL + 3840, vp + 10 * D_);
            if (c == 0) {
                DBG(14);
                if (EARLY) asm volatile("bar.sync 1, 384;" ::: "memory");
                else asm volatile("barrier.cluster.arrive.relaxed.aligned;\nbarrier.cluster.wait.aligned;" ::: "memory");
                DBG(1);
            }
            if (CPLAG && c < 3) __nanosleep(CPLAG);
            asm volatile("cp.async.mbarrier.arrive.noinc.shared::cta.b64 [%0];" ::"r"(bar + 8 * (B_LD + c)) : "memory");
        }
        if (EARLY) asm volatile("barrier.cluster.arrive.relaxed.aligned;\nbarrier.cluster.wait.aligned;" ::: "memory");
        asm volatile("setmaxnreg.inc.sync.aligned.u32 184;");
#pragma unroll 1
        for (int slot = wg; slot < ns; slot += 2) conv_slot(sb, slot, warp, lane, gridDim.y);
        DBG(9);
    } else {
        asm volatile("setmaxnreg.dec.sync.aligned.u32 72;");
        const int pw = wid - 8;
        auto load_filter = [&](int j) { bulk_g2s(sb + K_OFF + j * K_PITCH + 272, filt + (size_t)(c0 + 8 * j + rank) * S_, 4096, bar + 8 * (B_KF + (j >> 1))); };
        if (EARLY && pw < 4) {
            if (elect_one()) mbar_init(bar + 8 * (B_LD + pw), 256);
            __syncwarp();
            asm volatile("bar.arrive 1, 384;" ::: "memory");
        }
        if (elect_one()) {
#pragma unroll 1
            for (int i = EARLY && pw < 4 ? pw + 8 : pw; i < B_N; i += 8) {
                mbar_init(bar + 8 * i, i < B_KF ? 256 : i == B_ACK ? 8 : i >= B_ZF ? 4 : i == B_KR + 1 ? 6 : (i == B_LR || i == B_XF) ? 2 : 1);
                if (i == B_KF) { load_filter(0); load_filter(1); }
                if (i >= B_KF && i <= B_XF) mbar_expect(bar + 8 * i, i == B_XF ? 7 * 2560 : (int)((0x2411115122ull >> (4 * (i - B_KF))) & 15) * 4096);
            }
            asm volatile("fence.mbarrier_init.release.cluster;" ::: "memory");
        }
        __syncwarp();
        DBG(14);
        asm volatile("barrier.cluster.arrive.relaxed.aligned;" ::: "memory");
        asm volatile("barrier.cluster.wait.aligned;" ::: "memory");
        DBG(1);
        const uint32_t xr2 = sb + 89088;
        const int row0 = ns == 2 ? 1792 + rank * 32 : blockIdx.x * 16;
        const int ro = REMAP && (pw & 5) == 4 ? pw ^ 2 : pw;
        if (ro == 6) {
#pragma unroll 1
            for (int j = 0; j < ns; j++) {
                if (lane < 16) sts128u(sb + W_OFF + j * W_PITCH + lane * 16, 0, 0, 0, 0);
                if (lane < 17) sts128u(sb + K_OFF + j * K_PITCH + lane * 16, 0, 0, 0, 0);
            }
        }
        if (ro == 5 && lane == 0) asm volatile("prefetch.tensormap [%0];" ::"l"(&mp.x) : "memory");
        if (ro >= ns) mbar_wait(bar + 8 * B_LD, 0);
        if (ro < ns) {
            uint32_t la = sb + KV_OFF + ro * 16 + (((~lane & 1) << 2) + ((lane >> 1) & 3)) * 80 + (lane >> 3) * 640;
            uint32_t dst = mapa(sb + W_OFF + ro * W_PITCH + 256 + rank * 256 + (lane & 3) * 16, lane >> 2);
            uint32_t mb = mapa(bar + 8 * (ro < 2 ? B_UF : B_UF2 + (ro >> 2)), lane >> 2);
            uint32_t ca = sb + CF_OFF + ro * 64 + (lane >> 2) * 8;
            asm volatile("" : "+r"(la), "+r"(dst), "+r"(mb), "+r"(ca));
#pragma unroll 1
            for (int c = 0; c < 4; c++, la += KV_UNIT, dst += 2048, mb += ro < 2 ? 8 : 0) {
                mbar_wait(bar + 8 * (B_LD + c), 0);
                if (lane == 0) DBGH2(32 + (ro >> 1) * 64 + c * 2 + (ro & 1));
                uint32_t cw0, cw1;
                asm volatile("ld.shared.v2.b32 {%0,%1}, [%2];" : "=r"(cw0), "=r"(cw1) : "r"(ca));
                const uint32_t f0 = __byte_perm(cw0, 0, 0x1010), f1 = __byte_perm(cw0, 0, 0x3232), f2 = __byte_perm(cw1, 0, 0x1010), f3 = __byte_perm(cw1, 0, 0x3232);
                uint32_t kp[12], vp[12];
                ldsm4t(kp, la); ldsm4t(kp + 4, la + 2560); ldsm4t(kp + 8, la + 5120);
                ldsm4t(vp, la + V_REL); ldsm4t(vp + 4, la + V_REL + 2560);
                asm volatile("ldmatrix.sync.aligned.m8n8.x1.trans.shared.b16 {%0}, [%1];" : "=r"(vp[8]) : "r"(la + V_REL + 5120));
                uint32_t u[9];
                uint32_t ksp = __byte_perm(kp[1], kp[0], 0x5432);
#pragma unroll
                for (int i = 0; i < 9; i++) {
                    const uint32_t ks = __byte_perm(kp[i + 2], kp[i + 1], 0x5432);
                    u[i] = hmul2(hfma2(f0, kp[i + 2], hfma2(f1, ks, hfma2(f2, kp[i + 1], hmul2(f3, ksp)))), vp[i]);
                    ksp = ks;
                }
                if (c == 3 && lane == 0) mbar_arrive(bar + 8 * (B_KR + 1));
                if (ro >= 2 && c < PRIO) mbar_wait(bar + 8 * (B_UF + c), 0);
#pragma unroll
                for (int i = 0; i < 4; i++)
                    stas4((i & 2 ? dst ^ 32 : dst) + i * 64, __byte_perm(u[2 * i + 1], u[2 * i], 0x5432), u[2 * i + 1], __byte_perm(u[2 * i + 2], u[2 * i + 1], 0x5432), u[2 * i + 2], mb);
                if (lane == 0) DBGH2(40 + (ro >> 1) * 64 + c * 2 + (ro & 1));
            }
        } else if (ro == 5) {
            if (elect_one()) {
                if (FLAG_) mbar_wait(bar + 8 * (B_LD + FLAG_), 0);
#pragma unroll 1
                for (int j = 2; j < ns; j++) load_filter(j);
                if (ns > 2) mbar_wait(bar + 8 * (B_LD + XLAG), 0);
                else bulk_g2s(xr2, x + (size_t)(row0 + 16) * D_, 18432, bar + 8 * B_LR);
                if (!TFIRST) bulk_g2s(sb + XR_OFF, x + (size_t)row0 * D_, 18432, bar + 8 * B_LR);
#pragma unroll 1
                for (int c = 0; c < 4; c++) tma3d(sb + XS_OFF + c * 5120, &mp.x, c0, c * 32 + rank * 4, 0, bar + 8 * B_LX);
                if (TFIRST) bulk_g2s(sb + XR_OFF, x + (size_t)row0 * D_, 18432, bar + 8 * B_LR);
                mbar_expect(bar + 8 * B_LR, ns == 2 ? 36864 : 18432);
            }
        } else if (ro == 6) {
#pragma unroll 1
            for (int i = 0; 2 * i < ns; i++) {
                mbar_wait(bar + 8 * (B_KF + i), 0);
                if (lane < ns && (lane >> 1) == i) {
                    const uint32_t ka = sb + K_OFF + lane * K_PITCH + 272, k01 = lds32u(ka), dw = lds32u(sb + CF_OFF + 320 + lane * 16 + (rank >> 1) * 4);
                    asm volatile("st.shared.b16 [%0], %1;" ::"r"(ka), "h"((unsigned short)pack_bf16(bf_lo(k01) + ((rank & 1) ? bf_hi(dw) : bf_lo(dw)), 0.f)) : "memory");
                }
                fence_async_smem();
                __syncwarp();
                if (lane == 0) mbar_arrive(bar + 8 * (B_KR + i));
            }
        } else if (ro == 7) {
            const unsigned ep = lds32u(sb + CF_OFF + 400) + 1;
            if (ns == 2 || lane < 16) {
                asm volatile("st.relaxed.gpu.global.u32 [%0], %1;" ::"l"(sc->st1 + row0 + lane), "r"(~ep << 31) : "memory");
                sc->st2[row0 + lane] = make_uint4(~ep & 1, 0, 0, 0);
            }
            if (blockIdx.x == 0 && lane == 0) sc->epoch[0] = ep;
            __syncwarp();
            if (lane == 0) mbar_arrive(bar + 8 * B_LR);
            if (TRIG) mbar_wait(bar + 8 * (B_LD + TRIG), 0);
            asm volatile("griddepcontrol.launch_dependents;" ::: "memory");
        }
        __syncwarp();
        DBG(10);
        const unsigned ep = lds32u(sb + CF_OFF + 400) + 1;
        if (wg == 3) {
            const int rl = warp * 4 + (lane >> 3);
            mbar_wait(bar + 8 * B_LR, 0);
            DBG(8);
#pragma unroll 1
            for (int i = 0; i < (ns == 2 ? 2 : 1); i++) {
                const uint32_t a = (i ? xr2 : sb + XR_OFF) + rl * 1152 + (lane & 7) * 16;
                float s[4] = {}, q[4] = {};
#pragma unroll SUNR
                for (int k = 0; k < 9; k++) {
                    const uint4 v = lds128u(a + k * 128);
                    const uint32_t w[4] = {v.x, v.y, v.z, v.w};
#pragma unroll
                    for (int e = 0; e < 4; e++) {
                        const float d0 = bf_lo(w[e]), d1 = bf_hi(w[e]);
                        s[e] += d0 + d1; q[e] = fmaf(d0, d0, fmaf(d1, d1, q[e]));
                    }
                }
                float s0 = (s[0] + s[1]) + (s[2] + s[3]), q0 = (q[0] + q[1]) + (q[2] + q[3]);
#pragma unroll
                for (int d = 1; d < 8; d *= 2) { s0 += __shfl_xor_sync(0xffffffffu, s0, d); q0 += __shfl_xor_sync(0xffffffffu, q0, d); }
                s0 *= 1.f / D_;
                const uint32_t o = (pack_bf16(s0, rcp_fast(sqrt_fast(fmaxf(q0 * (1.f / D_) - s0 * s0, 0.f) + 1e-5f))) & 0x7fffffffu) | (ep << 31);
                if ((lane & 7) == 0) asm volatile("st.relaxed.gpu.global.u32 [%0], %1;" ::"l"(sc->st1 + row0 + i * 16 + rl), "r"(o) : "memory");
            }
            DBG(11);
        } else {
            const int dr = ((lane >> 2) - rank) & 7;
            const uint32_t la = sb + XS_OFF + pw * 5120 + (((lane & 1) << 2) + ((lane >> 1) & 3)) * 80 + (lane >> 3) * 640;
            const uint32_t oa = sb + (dr ? XO_OFF + (dr - 1) * XO_PITCH : XT_OFF + rank * 2560) + pw * 640 + (lane & 3) * 16;
            mbar_wait(bar + 8 * B_LX, 0);
            DBG(15);
            uint32_t xv[5][8];
#pragma unroll
            for (int i = 0; i < 5; i++) { ldsm4t(xv[i], la + i * 16); ldsm4t(xv[i] + 4, la + i * 16 + 2560); }
#pragma unroll
            for (int i = 0; i < 5; i++) {
                sts128u(oa + i * 128, xv[i][0], xv[i][1], xv[i][2], xv[i][3]);
                sts128u(oa + i * 128 + 64, xv[i][4], xv[i][5], xv[i][6], xv[i][7]);
            }
            fence_async_smem();
            asm volatile("bar.sync 3, 128;" ::: "memory");
            if (elect_one()) {
#pragma unroll 1
                for (int i = pw + 4; i >= 0; i -= 4) {
                    const int d = (rank + i) & 7;
                    if (i) asm volatile("cp.async.bulk.shared::cluster.shared::cta.mbarrier::complete_tx::bytes [%0], [%1], 2560, [%2];"
                                        ::"r"(mapa(sb + XT_OFF + rank * 2560, d)), "r"(sb + XO_OFF + (i - 1) * XO_PITCH), "r"(mapa(bar + 8 * B_XF, d)) : "memory");
                    else mbar_arrive(bar + 8 * B_XF);
                }
            }
        }
        __syncwarp();
        if (POLLW == 1) mbar_wait(bar + 8 * B_XF, 0);
        if (POLLW == 2) asm volatile("bar.sync 5, 256;" ::: "memory");
        DBG(12);
        const int b = threadIdx.x - 256;
        uint4 v0, v1;
#pragma unroll 1
        for (int it = 0; it < 1000000; it++) {
            asm volatile("ld.relaxed.gpu.global.v4.b32 {%0,%1,%2,%3}, [%4];" : "=r"(v0.x), "=r"(v0.y), "=r"(v0.z), "=r"(v0.w) : "l"(sc->st1 + b * 8) : "memory");
            asm volatile("ld.relaxed.gpu.global.v4.b32 {%0,%1,%2,%3}, [%4 + 16];" : "=r"(v1.x), "=r"(v1.y), "=r"(v1.z), "=r"(v1.w) : "l"(sc->st1 + b * 8) : "memory");
            const uint32_t e = ep << 31;
            if (!__any_sync(0xffffffffu, (int)(tagbad(v0.x, v0.y, e) | tagbad(v0.z, v0.w, e) | tagbad(v1.x, v1.y, e) | tagbad(v1.z, v1.w, e)) < 0)) break;
            __nanosleep(BACKOFF);
        }
        const uint4 mu = make_uint4(__byte_perm(v0.x, v0.y, 0x5410), __byte_perm(v0.z, v0.w, 0x5410), __byte_perm(v1.x, v1.y, 0x5410), __byte_perm(v1.z, v1.w, 0x5410));
        const uint4 rs = make_uint4(__byte_perm(v0.x, v0.y, 0x7632) & 0x7fff7fffu, __byte_perm(v0.z, v0.w, 0x7632) & 0x7fff7fffu,
                                    __byte_perm(v1.x, v1.y, 0x7632) & 0x7fff7fffu, __byte_perm(v1.z, v1.w, 0x7632) & 0x7fff7fffu);
        if (PFPOS == 1) {
            if (pw < 3 && blockIdx.x < 108 && elect_one())
                asm volatile("cp.async.bulk.prefetch.L2.global [%0], %1;" ::"l"(w1 + (size_t)(blockIdx.x * 3 + pw) * 8192), "r"(16384) : "memory");
            __syncwarp();
        }
        DBG(13);
        mbar_wait(bar + 8 * B_XF, 0);
        DBG(19);
        if (pw == 0 && lane < 8) mbar_arrive_cluster(mapa(bar + 8 * B_ACK, lane));
        uint32_t xa = sb + XT_OFF + ((b >> 3) & 7) * 2560 + (b >> 6) * 640 + (b & 1) * 64 + ((b >> 1) & 3) * 16;
        bf16* ho = sc->hT + (size_t)(c0 + rank) * S_ + b * 8;
        struct In { uint4 x, z0, z1, z2, z3; };
        auto fetch = [&](int slot) {
            In v;
            const uint32_t za = zbase(sb, slot) + b * 16;
            v.x = lds128u(xa + slot * 128);
            mbar_wait(bar + 8 * (B_ZF + slot * 2 + (wg & 1)), 0);
            v.z0 = lds128u(za); v.z1 = lds128u(za + Z_ARR); v.z2 = lds128u(za + 2 * Z_ARR); v.z3 = lds128u(za + 3 * Z_ARR);
            return v;
        };
        auto fin = [&](const In& v, int slot) {
            uint4 h;
            h.x = hfma2(hmul2(hsub2(v.x.x, mu.x), rs.x), hadd2(hadd2(v.z0.x, v.z1.x), hadd2(v.z2.x, v.z3.x)), v.x.x);
            h.y = hfma2(hmul2(hsub2(v.x.y, mu.y), rs.y), hadd2(hadd2(v.z0.y, v.z1.y), hadd2(v.z2.y, v.z3.y)), v.x.y);
            h.z = hfma2(hmul2(hsub2(v.x.z, mu.z), rs.z), hadd2(hadd2(v.z0.z, v.z1.z), hadd2(v.z2.z, v.z3.z)), v.x.z);
            h.w = hfma2(hmul2(hsub2(v.x.w, mu.w), rs.w), hadd2(hadd2(v.z0.w, v.z1.w), hadd2(v.z2.w, v.z3.w)), v.x.w);
            *(uint4*)(ho + slot * 8 * S_) = h;
        };
#pragma unroll 1
        for (int slot = 0; slot < ns; slot++) fin(fetch(slot), slot);
        if (pw == 0) mbar_wait(bar + 8 * B_ACK, 0);
        DBG(9); DBGT(31);
    }
}
}

typedef CUresult (*EncFn)(CUtensorMap*, CUtensorMapDataType, cuuint32_t, void*, const cuuint64_t*, const cuuint64_t*, const cuuint32_t*,
                          const cuuint32_t*, CUtensorMapInterleave, CUtensorMapSwizzle, CUtensorMapL2promotion, CUtensorMapFloatOOBfill);
static void enc(EncFn fn, CUtensorMap* m, int rank, const void* base, const cuuint64_t* dims, const cuuint64_t* strides, const cuuint32_t* box, CUtensorMapSwizzle sw) {
    cuuint32_t es[5] = {1, 1, 1, 1, 1};
    fn(m, CU_TENSOR_MAP_DATA_TYPE_BFLOAT16, rank, (void*)base, dims, strides, box, es, CU_TENSOR_MAP_INTERLEAVE_NONE, sw,
       CU_TENSOR_MAP_L2_PROMOTION_L2_128B, CU_TENSOR_MAP_FLOAT_OOB_FILL_NONE);
}

extern "C" void kernel_launch(void* const* d_in, const int* in_sizes, int n_in, void* d_out, int out_size) {
    const bf16 *x = (const bf16*)d_in[0], *k = (const bf16*)d_in[1], *v = (const bf16*)d_in[2], *sk = (const bf16*)d_in[3],
               *K = (const bf16*)d_in[4], *Dv = (const bf16*)d_in[5], *w1 = (const bf16*)d_in[7], *b1 = (const bf16*)d_in[8],
               *w2 = (const bf16*)d_in[9], *b2 = (const bf16*)d_in[10];
    bf16* out = (bf16*)d_out;
    void* fp = nullptr; cudaDriverEntryPointQueryResult q;
    cudaGetDriverEntryPoint("cuTensorMapEncodeTiled", &fp, cudaEnableDefault, &q);
    EncFn fn = (EncFn)fp;
    void* hT; cudaGetSymbolAddress(&hT, g_scratch);
    Scratch* sc = (Scratch*)hT;
    ffn::Maps mp;
    { cuuint64_t d[2] = {S_, D_}, s[1] = {S_ * 2}; cuuint32_t b[2] = {64, 64}; enc(fn, &mp.h, 2, hT, d, s, b, CU_TENSOR_MAP_SWIZZLE_128B); }
    { cuuint64_t d[3] = {32, D_, F_ / 32}, s[2] = {F_ * 2, 64}; cuuint32_t b[3] = {32, 64, 3}; enc(fn, &mp.w1[1], 3, w1, d, s, b, CU_TENSOR_MAP_SWIZZLE_64B); }
    { cuuint64_t d[3] = {64, D_, F_ / 64}, s[2] = {F_ * 2, 128};
      cuuint32_t b2_[3] = {64, 48, 2}; enc(fn, &mp.w1[2], 3, w1, d, s, b2_, CU_TENSOR_MAP_SWIZZLE_128B);
      cuuint32_t b3_[3] = {64, 96, 1}; enc(fn, &mp.w1[0], 3, w1, d, s, b3_, CU_TENSOR_MAP_SWIZZLE_128B); }
    { cuuint64_t d[2] = {D_, F_}, s[1] = {D_ * 2}; cuuint32_t b[2] = {64, 96}; enc(fn, &mp.w2, 2, w2, d, s, b, CU_TENSOR_MAP_SWIZZLE_128B); }
    cv::Maps cm;
    { cuuint64_t d[3] = {D_, S_ / 16, 16}, s[2] = {16 * D_ * 2, D_ * 2};
      cuuint32_t bm[3] = {40, 4, 16};
      enc(fn, &cm.x, 3, x, d, s, bm, CU_TENSOR_MAP_SWIZZLE_NONE); }
    cudaFuncSetAttribute(ffn::ffn_kernel, cudaFuncAttributeMaxDynamicSharedMemorySize, ffn::SMEM);
    cudaFuncSetAttribute(cv::conv_kernel, cudaFuncAttributeMaxDynamicSharedMemorySize, cv::SMEM);
    cudaStream_t st = cudaStreamPerThread;
    cv::conv_kernel<<<120, 512, cv::SMEM, st>>>(k, v, K, sk, Dv, sc, x, w1, cm);
    cudaLaunchConfig_t cf = {};
    cf.gridDim = dim3(132); cf.blockDim = dim3(384); cf.dynamicSmemBytes = ffn::SMEM; cf.stream = st;
    cudaLaunchAttribute at[1];
    at[0].id = cudaLaunchAttributeProgrammaticStreamSerialization; at[0].val.programmaticStreamSerializationAllowed = 1;
    cf.attrs = at; cf.numAttrs = 1;
    cudaLaunchKernelEx(&cf, ffn::ffn_kernel, sc, b1, w2, b2, out, mp);
}
```
